```python
import torch

def _softmax(x, axis=-1):
    return torch.softmax(x, dim=axis)
def _gelu(x):
    return torch.nn.functional.gelu(x, approximate="tanh")
def _silu(x):
    return torch.nn.functional.silu(x)
def _sigmoid(x):
    return torch.sigmoid(x)
def _layernorm(x, axis=-1, eps=1e-5):
    m = x.mean(dim=axis, keepdim=True)
    v = x.var(dim=axis, keepdim=True, unbiased=False)
    return (x - m) / torch.sqrt(v + eps)
def _scatter_add(tgt, idx, src, axis=0):
    return tgt.clone().index_add_(axis, idx, src)
def _segment_sum(src, seg, n):
    out = torch.zeros((n,) + src.shape[1:], dtype=src.dtype)
    return out.index_add_(0, seg, src)
def _pad(x, pw):
    flat = tuple(v for pair in reversed(pw) for v in pair)
    return torch.nn.functional.pad(x, flat)

kernel_name = 'concat_heads__linear_attn_block__grouped_kv_mqa__prompt'

def setup_inputs():

    _w = (lambda a: (lambda t: t.to(torch.bfloat16) if t.is_floating_point() else t)(torch.as_tensor(a)))
    def _A_setup():
        B, S, D = 1, 2048, 1024
        return {
            "x": _w((lambda *s: torch.randn(*s, dtype=torch.bfloat16) * 0.05)(B, S, D)),
            "wqkv": _w((lambda *s: torch.randn(*s, dtype=torch.bfloat16) * 0.8)(D, 3 * D)),
            "wo": _w((lambda *s: torch.randn(*s, dtype=torch.bfloat16) * 0.05)(D, D)),
        }
    _A_in = _A_setup()

    def _B_setup():
        B, S, D, H = 1, 2048, 1024, 32
        Dh = D // H
        return {
            "x": _w((lambda *s: torch.randn(*s, dtype=torch.bfloat16) * 0.05)(B, S, D)),
            "wq": _w((lambda *s: torch.randn(*s, dtype=torch.bfloat16) * 0.8)(D, H * Dh)),
            "wk": _w((lambda *s: torch.randn(*s, dtype=torch.bfloat16) * 0.8)(D, Dh)),
            "wv": _w((lambda *s: torch.randn(*s, dtype=torch.bfloat16) * 0.05)(D, Dh)),
            "wo": _w((lambda *s: torch.randn(*s, dtype=torch.bfloat16) * 0.05)(H * Dh, D)),
        }
    _B_in = _B_setup()

    return {
        "A_x": _A_in["x"],
        "A_wqkv": _A_in["wqkv"],
        "A_wo": _A_in["wo"],
        "B_x": _B_in["x"],
        "B_wq": _B_in["wq"],
        "B_wk": _B_in["wk"],
        "B_wv": _B_in["wv"],
        "B_wo": _B_in["wo"],
    }

def reference(A_x, A_wqkv, A_wo, B_x, B_wq, B_wk, B_wv, B_wo):
    def _A_ref(x, wqkv, wo):
        B, S, D = x.shape
        H = 32; Dh = D // H
        qkv = (lambda x, *d: x.permute(*d))((x @ wqkv).reshape(B, S, 3, H, Dh), 2, 0, 3, 1, 4)
        q, k, v = qkv[0], qkv[1], qkv[2]
        phi = lambda t: torch.where(t > 0, t + 1, torch.exp(t)) + 1e-6
        pq, pk = phi(q), phi(k)
        kv = torch.einsum("bhsd,bhse->bhde", pk, v)
        z = torch.einsum("bhsd->bhd", pk)
        num = torch.einsum("bhqd,bhde->bhqe", pq, kv)
        den = torch.einsum("bhqd,bhd->bhq", pq, z)[..., None] + 1e-6
        o = num / den
        return (lambda x, *d: x.permute(*d))(o, 0, 2, 1, 3).reshape(B, S, D) @ wo

    def _B_ref(x, wq, wk, wv, wo):
        B, S, D = x.shape
        H = 32
        Dh = D // H
        q = (lambda x, *d: x.permute(*d))((x @ wq).reshape(B, S, H, Dh), 0, 2, 1, 3)
        k = x @ wk
        v = x @ wv
        scores = torch.einsum("bhqd,bkd->bhqk", q, k) * (Dh ** -0.5)
        p = _softmax(scores, axis=-1)
        o = torch.einsum("bhqk,bkd->bhqd", p, v)
        return (lambda x, *d: x.permute(*d))(o, 0, 2, 1, 3).reshape(B, S, H * Dh) @ wo

    a = _A_ref(A_x, A_wqkv, A_wo)
    b = _B_ref(B_x, B_wq, B_wk, B_wv, B_wo)
    return torch.concatenate([a, b], axis=-1)
```

```cpp
#include <cuda_runtime.h>
#include <cuda_bf16.h>
#include <cuda.h>
#include <stdint.h>

#define PF 0
#define GATE 1
#define QBW 0
#define TAIL 0
#define PINAT 2
#define HPROMO CU_TENSOR_MAP_L2_PROMOTION_L2_128B
#define KVTMA 1
#define POLLNS 150
#define QRS 1
#define SKEW 0
#define ROLL 0
#define REG_S 40
#define REG_G 168
#define REG_A 152
#define WQPOS 7
#define WQPF 0
#define EARLYKV 1
#define PFD 0
#define HOLDQ 2
#define WKVLSU 0
#define GATEWQ 0
#define EARLYST 4
#define EARLYPOLL 1
#define WQ0 0
#define LATEQ 1
#define PFW 0
#define QSEL(a, b) a
namespace {

template<int TB> __device__ __forceinline__ void wgmma_rs_n32(float (&d)[16], uint32_t a0, uint32_t a1, uint32_t a2, uint32_t a3, uint64_t db, int sc){
  asm volatile("{\n.reg .pred p;\nsetp.ne.b32 p, %21, 0;\n"
  "wgmma.mma_async.sync.aligned.m64n32k16.f32.bf16.bf16 {%0,%1,%2,%3,%4,%5,%6,%7,%8,%9,%10,%11,%12,%13,%14,%15}, {%16,%17,%18,%19}, %20, p, 1, 1, %22;\n}\n"
  : "+f"(d[0]),"+f"(d[1]),"+f"(d[2]),"+f"(d[3]),"+f"(d[4]),"+f"(d[5]),"+f"(d[6]),"+f"(d[7]),
    "+f"(d[8]),"+f"(d[9]),"+f"(d[10]),"+f"(d[11]),"+f"(d[12]),"+f"(d[13]),"+f"(d[14]),"+f"(d[15])
  : "r"(a0), "r"(a1), "r"(a2), "r"(a3), "l"(db), "r"(sc), "n"(TB));
}
template<int TB> __device__ __forceinline__ void wgmma_rs_n40(float (&d)[20], uint32_t a0, uint32_t a1, uint32_t a2, uint32_t a3, uint64_t db, int sc){
  asm volatile("{\n.reg .pred p;\nsetp.ne.b32 p, %25, 0;\n"
  "wgmma.mma_async.sync.aligned.m64n40k16.f32.bf16.bf16 {%0,%1,%2,%3,%4,%5,%6,%7,%8,%9,%10,%11,%12,%13,%14,%15,%16,%17,%18,%19}, {%20,%21,%22,%23}, %24, p, 1, 1, %26;\n}\n"
  : "+f"(d[0]),"+f"(d[1]),"+f"(d[2]),"+f"(d[3]),"+f"(d[4]),"+f"(d[5]),"+f"(d[6]),"+f"(d[7]),
    "+f"(d[8]),"+f"(d[9]),"+f"(d[10]),"+f"(d[11]),"+f"(d[12]),"+f"(d[13]),"+f"(d[14]),"+f"(d[15]),
    "+f"(d[16]),"+f"(d[17]),"+f"(d[18]),"+f"(d[19])
  : "r"(a0), "r"(a1), "r"(a2), "r"(a3), "l"(db), "r"(sc), "n"(TB));
}
template<int TB> __device__ __forceinline__ void wgmma_rs_n40_z(float (&d)[20], uint32_t a0, uint32_t a1, uint32_t a2, uint32_t a3, uint64_t db){
  asm volatile("wgmma.mma_async.sync.aligned.m64n40k16.f32.bf16.bf16 {%0,%1,%2,%3,%4,%5,%6,%7,%8,%9,%10,%11,%12,%13,%14,%15,%16,%17,%18,%19}, {%20,%21,%22,%23}, %24, 0, 1, 1, %25;\n"
  : "=f"(d[0]),"=f"(d[1]),"=f"(d[2]),"=f"(d[3]),"=f"(d[4]),"=f"(d[5]),"=f"(d[6]),"=f"(d[7]),
    "=f"(d[8]),"=f"(d[9]),"=f"(d[10]),"=f"(d[11]),"=f"(d[12]),"=f"(d[13]),"=f"(d[14]),"=f"(d[15]),
    "=f"(d[16]),"=f"(d[17]),"=f"(d[18]),"=f"(d[19])
  : "r"(a0), "r"(a1), "r"(a2), "r"(a3), "l"(db), "n"(TB));
}
template<int TB> __device__ __forceinline__ void wgmma_rs_n64(float (&d)[32], uint32_t a0, uint32_t a1, uint32_t a2, uint32_t a3, uint64_t db, int sc){
  asm volatile("{\n.reg .pred p;\nsetp.ne.b32 p, %37, 0;\n"
  "wgmma.mma_async.sync.aligned.m64n64k16.f32.bf16.bf16 {%0,%1,%2,%3,%4,%5,%6,%7,%8,%9,%10,%11,%12,%13,%14,%15,%16,%17,%18,%19,%20,%21,%22,%23,%24,%25,%26,%27,%28,%29,%30,%31}, {%32,%33,%34,%35}, %36, p, 1, 1, %38;\n}\n"
  : "+f"(d[0]),"+f"(d[1]),"+f"(d[2]),"+f"(d[3]),"+f"(d[4]),"+f"(d[5]),"+f"(d[6]),"+f"(d[7]),
    "+f"(d[8]),"+f"(d[9]),"+f"(d[10]),"+f"(d[11]),"+f"(d[12]),"+f"(d[13]),"+f"(d[14]),"+f"(d[15]),
    "+f"(d[16]),"+f"(d[17]),"+f"(d[18]),"+f"(d[19]),"+f"(d[20]),"+f"(d[21]),"+f"(d[22]),"+f"(d[23]),
    "+f"(d[24]),"+f"(d[25]),"+f"(d[26]),"+f"(d[27]),"+f"(d[28]),"+f"(d[29]),"+f"(d[30]),"+f"(d[31])
  : "r"(a0), "r"(a1), "r"(a2), "r"(a3), "l"(db), "r"(sc), "n"(TB));
}
template<int TB> __device__ __forceinline__ void wgmma_rs_n64_z(float (&d)[32], uint32_t a0, uint32_t a1, uint32_t a2, uint32_t a3, uint64_t db){
  asm volatile("wgmma.mma_async.sync.aligned.m64n64k16.f32.bf16.bf16 {%0,%1,%2,%3,%4,%5,%6,%7,%8,%9,%10,%11,%12,%13,%14,%15,%16,%17,%18,%19,%20,%21,%22,%23,%24,%25,%26,%27,%28,%29,%30,%31}, {%32,%33,%34,%35}, %36, 0, 1, 1, %37;\n"
  : "=f"(d[0]),"=f"(d[1]),"=f"(d[2]),"=f"(d[3]),"=f"(d[4]),"=f"(d[5]),"=f"(d[6]),"=f"(d[7]),
    "=f"(d[8]),"=f"(d[9]),"=f"(d[10]),"=f"(d[11]),"=f"(d[12]),"=f"(d[13]),"=f"(d[14]),"=f"(d[15]),
    "=f"(d[16]),"=f"(d[17]),"=f"(d[18]),"=f"(d[19]),"=f"(d[20]),"=f"(d[21]),"=f"(d[22]),"=f"(d[23]),
    "=f"(d[24]),"=f"(d[25]),"=f"(d[26]),"=f"(d[27]),"=f"(d[28]),"=f"(d[29]),"=f"(d[30]),"=f"(d[31])
  : "r"(a0), "r"(a1), "r"(a2), "r"(a3), "l"(db), "n"(TB));
}
template<int TA,int TB> __device__ __forceinline__ void wgmma_ss_n128(float (&d)[64], uint64_t da, uint64_t db, int sc){
  asm volatile("{\n.reg .pred p;\nsetp.ne.b32 p, %66, 0;\n"
  "wgmma.mma_async.sync.aligned.m64n128k16.f32.bf16.bf16 {%0,%1,%2,%3,%4,%5,%6,%7,%8,%9,%10,%11,%12,%13,%14,%15,%16,%17,%18,%19,%20,%21,%22,%23,%24,%25,%26,%27,%28,%29,%30,%31,%32,%33,%34,%35,%36,%37,%38,%39,%40,%41,%42,%43,%44,%45,%46,%47,%48,%49,%50,%51,%52,%53,%54,%55,%56,%57,%58,%59,%60,%61,%62,%63}, %64, %65, p, 1, 1, %67, %68;\n}\n"
  : "+f"(d[0]),"+f"(d[1]),"+f"(d[2]),"+f"(d[3]),"+f"(d[4]),"+f"(d[5]),"+f"(d[6]),"+f"(d[7]),
    "+f"(d[8]),"+f"(d[9]),"+f"(d[10]),"+f"(d[11]),"+f"(d[12]),"+f"(d[13]),"+f"(d[14]),"+f"(d[15]),
    "+f"(d[16]),"+f"(d[17]),"+f"(d[18]),"+f"(d[19]),"+f"(d[20]),"+f"(d[21]),"+f"(d[22]),"+f"(d[23]),
    "+f"(d[24]),"+f"(d[25]),"+f"(d[26]),"+f"(d[27]),"+f"(d[28]),"+f"(d[29]),"+f"(d[30]),"+f"(d[31]),
    "+f"(d[32]),"+f"(d[33]),"+f"(d[34]),"+f"(d[35]),"+f"(d[36]),"+f"(d[37]),"+f"(d[38]),"+f"(d[39]),
    "+f"(d[40]),"+f"(d[41]),"+f"(d[42]),"+f"(d[43]),"+f"(d[44]),"+f"(d[45]),"+f"(d[46]),"+f"(d[47]),
    "+f"(d[48]),"+f"(d[49]),"+f"(d[50]),"+f"(d[51]),"+f"(d[52]),"+f"(d[53]),"+f"(d[54]),"+f"(d[55]),
    "+f"(d[56]),"+f"(d[57]),"+f"(d[58]),"+f"(d[59]),"+f"(d[60]),"+f"(d[61]),"+f"(d[62]),"+f"(d[63])
  : "l"(da), "l"(db), "r"(sc), "n"(TA), "n"(TB));
}
template<int TA,int TB> __device__ __forceinline__ void wgmma_ss_n128_z(float (&d)[64], uint64_t da, uint64_t db){
  asm volatile("wgmma.mma_async.sync.aligned.m64n128k16.f32.bf16.bf16 {%0,%1,%2,%3,%4,%5,%6,%7,%8,%9,%10,%11,%12,%13,%14,%15,%16,%17,%18,%19,%20,%21,%22,%23,%24,%25,%26,%27,%28,%29,%30,%31,%32,%33,%34,%35,%36,%37,%38,%39,%40,%41,%42,%43,%44,%45,%46,%47,%48,%49,%50,%51,%52,%53,%54,%55,%56,%57,%58,%59,%60,%61,%62,%63}, %64, %65, 0, 1, 1, %66, %67;\n"
  : "=f"(d[0]),"=f"(d[1]),"=f"(d[2]),"=f"(d[3]),"=f"(d[4]),"=f"(d[5]),"=f"(d[6]),"=f"(d[7]),
    "=f"(d[8]),"=f"(d[9]),"=f"(d[10]),"=f"(d[11]),"=f"(d[12]),"=f"(d[13]),"=f"(d[14]),"=f"(d[15]),
    "=f"(d[16]),"=f"(d[17]),"=f"(d[18]),"=f"(d[19]),"=f"(d[20]),"=f"(d[21]),"=f"(d[22]),"=f"(d[23]),
    "=f"(d[24]),"=f"(d[25]),"=f"(d[26]),"=f"(d[27]),"=f"(d[28]),"=f"(d[29]),"=f"(d[30]),"=f"(d[31]),
    "=f"(d[32]),"=f"(d[33]),"=f"(d[34]),"=f"(d[35]),"=f"(d[36]),"=f"(d[37]),"=f"(d[38]),"=f"(d[39]),
    "=f"(d[40]),"=f"(d[41]),"=f"(d[42]),"=f"(d[43]),"=f"(d[44]),"=f"(d[45]),"=f"(d[46]),"=f"(d[47]),
    "=f"(d[48]),"=f"(d[49]),"=f"(d[50]),"=f"(d[51]),"=f"(d[52]),"=f"(d[53]),"=f"(d[54]),"=f"(d[55]),
    "=f"(d[56]),"=f"(d[57]),"=f"(d[58]),"=f"(d[59]),"=f"(d[60]),"=f"(d[61]),"=f"(d[62]),"=f"(d[63])
  : "l"(da), "l"(db), "n"(TA), "n"(TB));
}
template<int TA,int TB> __device__ __forceinline__ void wgmma_ss_n16(float (&d)[8], uint64_t da, uint64_t db, int sc){
  asm volatile("{\n.reg .pred p;\nsetp.ne.b32 p, %10, 0;\n"
  "wgmma.mma_async.sync.aligned.m64n16k16.f32.bf16.bf16 {%0,%1,%2,%3,%4,%5,%6,%7}, %8, %9, p, 1, 1, %11, %12;\n}\n"
  : "+f"(d[0]),"+f"(d[1]),"+f"(d[2]),"+f"(d[3]),"+f"(d[4]),"+f"(d[5]),"+f"(d[6]),"+f"(d[7])
  : "l"(da), "l"(db), "r"(sc), "n"(TA), "n"(TB));
}
template<int TA,int TB> __device__ __forceinline__ void wgmma_ss_n64(float (&d)[32], uint64_t da, uint64_t db, int sc){
  asm volatile("{\n.reg .pred p;\nsetp.ne.b32 p, %34, 0;\n"
  "wgmma.mma_async.sync.aligned.m64n64k16.f32.bf16.bf16 {%0,%1,%2,%3,%4,%5,%6,%7,%8,%9,%10,%11,%12,%13,%14,%15,%16,%17,%18,%19,%20,%21,%22,%23,%24,%25,%26,%27,%28,%29,%30,%31}, %32, %33, p, 1, 1, %35, %36;\n}\n"
  : "+f"(d[0]),"+f"(d[1]),"+f"(d[2]),"+f"(d[3]),"+f"(d[4]),"+f"(d[5]),"+f"(d[6]),"+f"(d[7]),
    "+f"(d[8]),"+f"(d[9]),"+f"(d[10]),"+f"(d[11]),"+f"(d[12]),"+f"(d[13]),"+f"(d[14]),"+f"(d[15]),
    "+f"(d[16]),"+f"(d[17]),"+f"(d[18]),"+f"(d[19]),"+f"(d[20]),"+f"(d[21]),"+f"(d[22]),"+f"(d[23]),
    "+f"(d[24]),"+f"(d[25]),"+f"(d[26]),"+f"(d[27]),"+f"(d[28]),"+f"(d[29]),"+f"(d[30]),"+f"(d[31])
  : "l"(da), "l"(db), "r"(sc), "n"(TA), "n"(TB));
}
template<int TA,int TB> __device__ __forceinline__ void wgmma_ss_n64_z(float (&d)[32], uint64_t da, uint64_t db){
  asm volatile("wgmma.mma_async.sync.aligned.m64n64k16.f32.bf16.bf16 {%0,%1,%2,%3,%4,%5,%6,%7,%8,%9,%10,%11,%12,%13,%14,%15,%16,%17,%18,%19,%20,%21,%22,%23,%24,%25,%26,%27,%28,%29,%30,%31}, %32, %33, 0, 1, 1, %34, %35;\n"
  : "=f"(d[0]),"=f"(d[1]),"=f"(d[2]),"=f"(d[3]),"=f"(d[4]),"=f"(d[5]),"=f"(d[6]),"=f"(d[7]),
    "=f"(d[8]),"=f"(d[9]),"=f"(d[10]),"=f"(d[11]),"=f"(d[12]),"=f"(d[13]),"=f"(d[14]),"=f"(d[15]),
    "=f"(d[16]),"=f"(d[17]),"=f"(d[18]),"=f"(d[19]),"=f"(d[20]),"=f"(d[21]),"=f"(d[22]),"=f"(d[23]),
    "=f"(d[24]),"=f"(d[25]),"=f"(d[26]),"=f"(d[27]),"=f"(d[28]),"=f"(d[29]),"=f"(d[30]),"=f"(d[31])
  : "l"(da), "l"(db), "n"(TA), "n"(TB));
}

constexpr uint32_t SB     = 1024;
constexpr uint32_t SM_X   = SB;
constexpr uint32_t SM_W0  = SB + 65536;
constexpr uint32_t SM_W1  = SB + 98304;
constexpr uint32_t SM_KV  = SB + 131072;
constexpr uint32_t SM_Q   = SB + 196608;
__host__ __device__ constexpr uint32_t head_wq(uint32_t st) {
  return st == 0 ? SM_KV + 32768 : (st == 1 || st == 5) ? SM_KV + 49152 : (st == 2 || st == 7) ? SM_Q : st == 6 ? SB + 32768 : SB + (st - 3) * 16384;
}
constexpr uint32_t SM_BAR = SB + 229376;
constexpr uint32_t SMEM_BYTES = 229376 + 768;
constexpr uint32_t B_FULL = SM_BAR, B_EMPTY = SM_BAR + 32, B_KVFULL = SM_BAR + 64, B_KVEMPTY = SM_BAR + 96;
constexpr uint32_t B_HX = SM_BAR + 256, B_HW = SM_BAR + 320, B_HE = SM_BAR + 384, B_HD0 = SM_BAR + 408, B_HD1 = SM_BAR + 416, B_KINFO = SM_BAR + 424, B_FLAGSET = SM_BAR + 432;
constexpr uint32_t B_QRDY = SM_BAR + 128, B_GPART = SM_BAR + 136, B_GSTORE = SM_BAR + 144, B_OSTORE = SM_BAR + 152;
constexpr uint32_t SM_WMAX = SM_BAR + 176, SM_KINFO = SM_BAR + 208, SM_UNSAFE = SM_BAR + 212, SM_DUMMY = SM_BAR + 224;

constexpr int F_KVB = 0;
constexpr int F_CNT = 128;
constexpr int C_PART = 0, C_RED = 16, C_OA = 24, C_OB = 40, C_DONE = 104, C_NUM = 105;
struct Small {
  uint32_t flags[4096];
  __nv_bfloat16 kvb[2048 * 64];
  uint32_t blob[8 * 4096];
  float zpart[16 * 16 * 64];
};
__device__ __align__(1024) Small g_small;
__device__ __align__(1024) __nv_bfloat16 g_oa[2048 * 1024];
__device__ __align__(1024) __nv_bfloat16 g_ob[2048 * 1024];
__device__ __align__(1024) float4 g_part[16 * 16 * 512];
static_assert(F_CNT + C_NUM * 32 <= 4096, "flags");
#define g_flags (g_small.flags)
#define g_kvb (g_small.kvb)
#define g_blob (g_small.blob)
#define g_zpart (g_small.zpart)
#define TLREC(k)
#define TLREC0(k)

struct Maps {
  const char* in[8];
  CUtensorMap xBh, wqh, wk, wv, kvS, xA, xB, wqkv, woA, wq, woB, kvb, oaL, oaS, obL, obS, out;
};

__device__ __forceinline__ void wg_fence() { asm volatile("wgmma.fence.sync.aligned;" ::: "memory"); }
__device__ __forceinline__ void wg_commit() { asm volatile("wgmma.commit_group.sync.aligned;" ::: "memory"); }
template <int N> __device__ __forceinline__ void wg_wait() { asm volatile("wgmma.wait_group.sync.aligned %0;" ::"n"(N) : "memory"); }
template <int N> __device__ __forceinline__ void pin(float (&d)[N]) {
#pragma unroll
  for (int i = 0; i < N; i++) asm volatile("" : "+f"(d[i])::"memory");
}
template <int N> __device__ __forceinline__ void pin(uint32_t (&d)[N]) {
#pragma unroll
  for (int i = 0; i < N; i++) asm volatile("" : "+r"(d[i])::"memory");
}
__device__ __forceinline__ uint64_t mkdesc(uint32_t a16, uint32_t lbo, uint32_t sbo, uint32_t sw) {
  uint32_t lo = a16 + ((lbo >> 4) << 16), hi = (sbo >> 4) | (sw << 30);
  uint64_t d;
  asm("mov.b64 %0,{%1,%2};" : "=l"(d) : "r"(lo), "r"(hi));
  return d;
}
__device__ __forceinline__ uint64_t descK(uint32_t a16) { return mkdesc(a16, 16, 1024, 1); }
__device__ __forceinline__ uint64_t descK64(uint32_t a16) { return mkdesc(a16, 16, 512, 2); }
__device__ __forceinline__ uint64_t descMN(uint32_t a16) { return mkdesc(a16, 32768, 1024, 1); }

__device__ __forceinline__ float ex2(float x) { float y; asm("ex2.approx.ftz.f32 %0,%1;" : "=f"(y) : "f"(x)); return y; }
__device__ __forceinline__ float rcp(float x) { float y; asm("rcp.approx.ftz.f32 %0,%1;" : "=f"(y) : "f"(x)); return y; }
__device__ __forceinline__ uint32_t pack(float lo, float hi) { uint32_t r; asm("cvt.rn.bf16x2.f32 %0,%1,%2;" : "=r"(r) : "f"(hi), "f"(lo)); return r; }
__device__ __forceinline__ float phi(float t) { return (t > 0.f ? t + 1.f : ex2(t * 1.4426950408889634f)) + 1e-6f; }

__device__ __forceinline__ void mbar_init(uint32_t b, uint32_t n) { asm volatile("mbarrier.init.shared::cta.b64 [%0],%1;" ::"r"(b), "r"(n) : "memory"); }
__device__ __forceinline__ void mbar_arrive(uint32_t b) { asm volatile("mbarrier.arrive.shared::cta.b64 _,[%0];" ::"r"(b) : "memory"); }
__device__ __forceinline__ void mbar_arrive_if(uint32_t b, bool p) {
  asm volatile("{\n.reg .pred p;\nsetp.ne.u32 p,%1,0;\n@p mbarrier.arrive.shared::cta.b64 _,[%0];\n}" ::"r"(b), "r"((uint32_t)p) : "memory");
}
__device__ __forceinline__ uint32_t mbar_test(uint32_t b, uint32_t parity) {
  uint32_t ok;
  asm volatile("{\n.reg .pred p;\nmbarrier.test_wait.parity.shared::cta.b64 p,[%1],%2;\nselp.u32 %0,1,0,p;\n}" : "=r"(ok) : "r"(b), "r"(parity) : "memory");
  return ok;
}
__device__ __forceinline__ void mbar_expect(uint32_t b, uint32_t bytes) {
  asm volatile("mbarrier.arrive.expect_tx.shared::cta.b64 _,[%0],%1;" ::"r"(b), "r"(bytes) : "memory");
}
#define SPIN_FAIL(n, x) if (++n > 4000000u) __trap();
__device__ __forceinline__ void mbar_wait(uint32_t b, uint32_t parity) {
  asm volatile(
      "{\n.reg .pred p;\n.reg .u32 t0;\n"
      "mbarrier.try_wait.parity.shared::cta.b64 p,[%0],%1;\n"
      "@p bra MW_DONE;\n"
      "mov.u32 t0,0;\n"
      "MW_LOOP:\n"
      "mbarrier.try_wait.parity.shared::cta.b64 p,[%0],%1,100000;\n"
      "@p bra MW_DONE;\n"
      "add.u32 t0,t0,1;\n"
      "setp.lt.u32 p,t0,20000;\n"
      "@p bra MW_LOOP;\n"
      "trap;\n"
      "MW_DONE:\n}" ::"r"(b), "r"(parity) : "memory");
}
__device__ __forceinline__ bool elect_one() {
  uint32_t p;
  asm volatile("{\n.reg .pred p;\nelect.sync _|p,0xffffffff;\nselp.u32 %0,1,0,p;\n}" : "=r"(p));
  return p != 0;
}
__device__ __forceinline__ void bar_sync(uint32_t id) { asm volatile("bar.sync %0,128;" ::"r"(id) : "memory"); }
__device__ __forceinline__ void fence_async_smem() { asm volatile("fence.proxy.async.shared::cta;" ::: "memory"); }
__device__ __forceinline__ void fence_async_gmem() { asm volatile("fence.proxy.async.global;" ::: "memory"); }
__device__ __forceinline__ void fence_acquire() { asm volatile("fence.acquire.gpu;" ::: "memory"); }
__device__ __forceinline__ void l2_prefetch(const void* p, uint32_t bytes) { asm volatile("cp.async.bulk.prefetch.L2.global [%0],%1;" ::"l"(p), "r"(bytes) : "memory"); }

__device__ __forceinline__ void tma2d(uint32_t dst, const CUtensorMap* m, int c0, int c1, uint32_t bar) {
  asm volatile("cp.async.bulk.tensor.2d.shared::cluster.global.mbarrier::complete_tx::bytes [%0],[%1,{%3,%4}],[%2];"
               ::"r"(dst), "l"(m), "r"(bar), "r"(c0), "r"(c1) : "memory");
}
__device__ __forceinline__ void tma2d_prefetch(const CUtensorMap* m, int c0, int c1) {
  asm volatile("cp.async.bulk.prefetch.tensor.2d.L2.global [%0,{%1,%2}];" ::"l"(m), "r"(c0), "r"(c1) : "memory");
}
__device__ __forceinline__ void tma3d(uint32_t dst, const CUtensorMap* m, int c0, int c1, int c2, uint32_t bar) {
  asm volatile("cp.async.bulk.tensor.3d.shared::cluster.global.mbarrier::complete_tx::bytes [%0],[%1,{%3,%4,%5}],[%2];"
               ::"r"(dst), "l"(m), "r"(bar), "r"(c0), "r"(c1), "r"(c2) : "memory");
}
__device__ __forceinline__ void tma4d(uint32_t dst, const CUtensorMap* m, int c0, int c1, int c2, int c3, uint32_t bar) {
  asm volatile("cp.async.bulk.tensor.4d.shared::cluster.global.mbarrier::complete_tx::bytes [%0],[%1,{%3,%4,%5,%6}],[%2];"
               ::"r"(dst), "l"(m), "r"(bar), "r"(c0), "r"(c1), "r"(c2), "r"(c3) : "memory");
}
__device__ __forceinline__ void tma_store2d(const CUtensorMap* m, int c0, int c1, uint32_t src) {
  asm volatile("cp.async.bulk.tensor.2d.global.shared::cta.bulk_group [%0,{%2,%3}],[%1];" ::"l"(m), "r"(src), "r"(c0), "r"(c1) : "memory");
}
__device__ __forceinline__ void bulk_load(uint32_t dst, const void* src, uint32_t bytes, uint32_t bar) {
  asm volatile("cp.async.bulk.shared::cluster.global.mbarrier::complete_tx::bytes [%0],[%1],%2,[%3];" ::"r"(dst), "l"(src), "r"(bytes), "r"(bar) : "memory");
}
__device__ __forceinline__ void bulk_commit() { asm volatile("cp.async.bulk.commit_group;" ::: "memory"); }
__device__ __forceinline__ void bulk_wait_read() { asm volatile("cp.async.bulk.wait_group.read 0;" ::: "memory"); }
__device__ __forceinline__ void bulk_wait_all() { asm volatile("cp.async.bulk.wait_group 0;" ::: "memory"); }
__device__ __forceinline__ void prefetch_map(const CUtensorMap* m) { asm volatile("prefetch.tensormap [%0];" ::"l"(m) : "memory"); }
__device__ __forceinline__ void stsm4(uint32_t a, uint32_t r0, uint32_t r1, uint32_t r2, uint32_t r3) {
  asm volatile("stmatrix.sync.aligned.m8n8.x4.shared.b16 [%0],{%1,%2,%3,%4};" ::"r"(a), "r"(r0), "r"(r1), "r"(r2), "r"(r3) : "memory");
}
__device__ __forceinline__ uint32_t* cnt_ptr(int c) { return g_flags + F_CNT + c * 32; }
__device__ __forceinline__ void cnt_add(int c) { asm volatile("red.release.gpu.global.add.u32 [%0],1;" ::"l"(cnt_ptr(c)) : "memory"); }
__device__ __forceinline__ uint32_t cnt_ld(int c) {
  uint32_t v;
  asm volatile("ld.acquire.gpu.global.u32 %0,[%1];" : "=r"(v) : "l"(cnt_ptr(c)) : "memory");
  return v;
}
__device__ __forceinline__ void cnt_wait(int c, uint32_t target) {
  uint32_t n = 0;
  while (cnt_ld(c) < target) {
    __nanosleep(40);
    SPIN_FAIL(n, c)
  }
}

template <bool TR, bool FIRST>
__device__ __forceinline__ void gemm_stage(float (&a0)[64], float (&a1)[64], uint32_t n, bool more, bool leader) {
  const uint32_t s = n & 3;
  const uint32_t x = (SM_X >> 4) + s * 1024, w = (SM_W0 >> 4) + s * 512;
  wg_fence();
#pragma unroll
  for (int kk = 0; kk < 4; kk++) {
    if (FIRST && kk == 0) {
      if (TR) wgmma_ss_n128_z<1, 0>(a0, descMN(w), descK(x)); else wgmma_ss_n128_z<0, 1>(a0, descK(x), descMN(w));
    } else {
      if (TR) wgmma_ss_n128<1, 0>(a0, descMN(w + kk * 128), descK(x + kk * 2), 1);
      else wgmma_ss_n128<0, 1>(a0, descK(x + kk * 2), descMN(w + kk * 128), 1);
    }
    wg_commit();
    wg_wait<1>();
    if (!FIRST && kk == 0) mbar_arrive_if(B_EMPTY + ((n - 1) & 3) * 8, leader);
    if (FIRST && kk == 0) {
      if (TR) wgmma_ss_n128_z<1, 0>(a1, descMN(w + 2048), descK(x)); else wgmma_ss_n128_z<0, 1>(a1, descK(x + 512), descMN(w));
    } else {
      if (TR) wgmma_ss_n128<1, 0>(a1, descMN(w + 2048 + kk * 128), descK(x + kk * 2), 1);
      else wgmma_ss_n128<0, 1>(a1, descK(x + 512 + kk * 2), descMN(w + kk * 128), 1);
    }
    wg_commit();
    if (kk == 3 && more) mbar_wait(B_FULL + ((n + 1) & 3) * 8, ((n + 1) >> 2) & 1);
    wg_wait<1>();
  }
}
template <bool TR>
__device__ __forceinline__ void gemm_tile(float (&a0)[64], float (&a1)[64], uint32_t n0, bool leader, uint32_t steps = 16) {
  mbar_wait(B_FULL + (n0 & 3) * 8, (n0 >> 2) & 1);
  gemm_stage<TR, true>(a0, a1, n0, true, leader);
#pragma unroll 1
  for (uint32_t n = n0 + 1; n < n0 + steps; n++) gemm_stage<TR, false>(a0, a1, n, n + 1 < n0 + steps, leader);
  wg_wait<0>();
  pin(a0);
  pin(a1);
}

template <int P>
__device__ __forceinline__ void final_mma(float (&a)[32], int lo, int hi) {
#pragma unroll
  for (int t = lo; t < hi; t++) {
    const uint32_t s = ((t >> 2) + 1) & 3, kk = t & 3;
    wgmma_ss_n64<0, 1>(a, descK((SM_X >> 4) + s * 1024 + (P >> 1) * 512 + kk * 2), descMN((SM_W0 >> 4) + (P & 1) * 2048 + s * 512 + kk * 128), 1);
  }
}
template <int P>
__device__ __forceinline__ void final_store(float (&a)[32], uint32_t sts, const CUtensorMap* m, int i, int j, bool issuer) {
  pin(a);
#pragma unroll
  for (int g = 0; g < 4; g++)
    stsm4(SM_KV + P * 8192 + (sts ^ (g << 5)), pack(a[8 * g], a[8 * g + 1]), pack(a[8 * g + 2], a[8 * g + 3]),
          pack(a[8 * g + 4], a[8 * g + 5]), pack(a[8 * g + 6], a[8 * g + 7]));
  fence_async_smem();
  bar_sync(1);
  if (issuer && elect_one()) {
    tma_store2d(m, 1024 + j * 128 + (P & 1) * 64, i * 128 + (P >> 1) * 64, SM_KV + P * 8192);
    bulk_commit();
  }
}
template <bool FIRST>
__device__ __forceinline__ void qb_stage(float (&a0)[64], float (&a1)[32], uint32_t n, uint32_t hf, bool more, bool leader) {
  const uint32_t s = n & 3;
  const uint32_t x1 = (SM_X >> 4) + s * 1024 + hf * 512, x0 = x1 ^ 512, w = (SM_W0 >> 4) + s * 512;
  wg_fence();
#pragma unroll
  for (int kk = 0; kk < 4; kk++) {
    if (FIRST && kk == 0) wgmma_ss_n128_z<0, 1>(a0, descK(x0), descMN(w));
    else wgmma_ss_n128<0, 1>(a0, descK(x0 + kk * 2), descMN(w + kk * 128), 1);
    if (FIRST && kk == 0) wgmma_ss_n64_z<0, 1>(a1, descK(x1), descMN(w + 2048));
    else wgmma_ss_n64<0, 1>(a1, descK(x1 + kk * 2), descMN(w + 2048 + kk * 128), 1);
    wg_commit();
    if (kk == 3 && more) mbar_wait(B_FULL + ((n + 1) & 3) * 8, ((n + 1) >> 2) & 1);
    wg_wait<QBW>();
    if (!FIRST && kk == 0) mbar_arrive_if(B_EMPTY + ((n - 1) & 3) * 8, leader);
  }
}
__device__ __forceinline__ uint32_t q_block(const float* acc, uint32_t qa, uint32_t m) {
  const float c = 0.17677669529663687f * 1.4426950408889634f;
  float v[16];
#pragma unroll
  for (int e = 0; e < 16; e++) v[e] = acc[e] * c;
  stsm4(qa, pack(v[0], v[1]), pack(v[2], v[3]), pack(v[4], v[5]), pack(v[6], v[7]));
  stsm4(qa ^ 32, pack(v[8], v[9]), pack(v[10], v[11]), pack(v[12], v[13]), pack(v[14], v[15]));
  float s0 = 0.f, s1 = 0.f;
#pragma unroll
  for (int g = 0; g < 4; g++) {
    s0 = fmaf(v[4 * g], v[4 * g], fmaf(v[4 * g + 1], v[4 * g + 1], s0));
    s1 = fmaf(v[4 * g + 2], v[4 * g + 2], fmaf(v[4 * g + 3], v[4 * g + 3], s1));
  }
  s0 += __shfl_xor_sync(~0u, s0, 1); s1 += __shfl_xor_sync(~0u, s1, 1);
  s0 += __shfl_xor_sync(~0u, s0, 2); s1 += __shfl_xor_sync(~0u, s1, 2);
  return max(m, max(__float_as_uint(s0), __float_as_uint(s1)));
}
__device__ __forceinline__ bool bound_exceeded(uint32_t qn2_bits) {
  float kn2;
  asm volatile("ld.shared.f32 %0,[%1];" : "=f"(kn2) : "r"(SM_KINFO) : "memory");
  return !(__uint_as_float(qn2_bits) * kn2 <= 3500.f);
}
__device__ __forceinline__ uint32_t wg_any(bool v) {
  uint32_t r;
  asm volatile("{\n.reg .pred p,q;\nsetp.ne.u32 p,%1,0;\nbar.red.or.pred q,1,128,p;\nselp.u32 %0,1,0,q;\n}" : "=r"(r) : "r"((uint32_t)v) : "memory");
  return r;
}

__device__ __forceinline__ void attn_batch(float (&S)[32], uint32_t q16, uint32_t k16, float (&O)[16], uint32_t (&P)[16], uint32_t v16, int acc) {
  wg_fence();
  wgmma_rs_n32<1>(O, P[0], P[1], P[2], P[3], descMN(v16 + 4), acc);
  wgmma_ss_n64_z<0, 0>(S, descK64(q16), descK(k16));
  wgmma_rs_n32<1>(O, P[4], P[5], P[6], P[7], descMN(v16 + 4 + 128), 1);
  wgmma_ss_n64<0, 0>(S, descK64(q16 + 2), descK(k16 + 2), 1);
  wgmma_rs_n32<1>(O, P[8], P[9], P[10], P[11], descMN(v16 + 4 + 256), 1);
  wgmma_rs_n32<1>(O, P[12], P[13], P[14], P[15], descMN(v16 + 4 + 384), 1);
  wg_commit();
}
__device__ __forceinline__ void attn_batch_rs(float (&S)[32], uint32_t (&q)[8], uint32_t k16, float (&O)[16], uint32_t (&P)[16], uint32_t v16, int acc) {
  wg_fence();
  wgmma_rs_n32<1>(O, P[0], P[1], P[2], P[3], descMN(v16 + 4), acc);
  wgmma_rs_n64_z<0>(S, q[0], q[1], q[2], q[3], descK(k16));
  wgmma_rs_n32<1>(O, P[4], P[5], P[6], P[7], descMN(v16 + 4 + 128), 1);
  wgmma_rs_n64<0>(S, q[4], q[5], q[6], q[7], descK(k16 + 2), 1);
  wgmma_rs_n32<1>(O, P[8], P[9], P[10], P[11], descMN(v16 + 4 + 256), 1);
  wgmma_rs_n32<1>(O, P[12], P[13], P[14], P[15], descMN(v16 + 4 + 384), 1);
  wg_commit();
}
__device__ __forceinline__ void attn_g1(float (&S)[32], uint32_t (&q)[8], uint32_t k16, float (&O)[16], uint32_t (&P)[16], uint32_t v16, int acc) {
  wg_fence();
  wgmma_rs_n32<1>(O, P[0], P[1], P[2], P[3], descMN(v16 + 4), acc);
  wgmma_rs_n64_z<0>(S, q[0], q[1], q[2], q[3], descK(k16));
  wgmma_rs_n32<1>(O, P[4], P[5], P[6], P[7], descMN(v16 + 4 + 128), 1);
  wgmma_rs_n64<0>(S, q[4], q[5], q[6], q[7], descK(k16 + 2), 1);
  wg_commit();
}
__device__ __forceinline__ void attn_g1(float (&S)[32], uint32_t q16, uint32_t k16, float (&O)[16], uint32_t (&P)[16], uint32_t v16, int acc) {
  wg_fence();
  wgmma_rs_n32<1>(O, P[0], P[1], P[2], P[3], descMN(v16 + 4), acc);
  wgmma_ss_n64_z<0, 0>(S, descK64(q16), descK(k16));
  wgmma_rs_n32<1>(O, P[4], P[5], P[6], P[7], descMN(v16 + 4 + 128), 1);
  wgmma_ss_n64<0, 0>(S, descK64(q16 + 2), descK(k16 + 2), 1);
  wg_commit();
}
__device__ __forceinline__ void attn_g2(float (&O)[16], uint32_t (&P)[16], uint32_t v16) {
  wgmma_rs_n32<1>(O, P[8], P[9], P[10], P[11], descMN(v16 + 4 + 256), 1);
  wgmma_rs_n32<1>(O, P[12], P[13], P[14], P[15], descMN(v16 + 4 + 384), 1);
  wg_commit();
}
__device__ __forceinline__ void load_q(uint32_t (&q)[8], uint32_t a) {
  asm volatile("ldmatrix.sync.aligned.m8n8.x4.shared.b16 {%0,%1,%2,%3},[%4];" : "=r"(q[0]), "=r"(q[1]), "=r"(q[2]), "=r"(q[3]) : "r"(a) : "memory");
  asm volatile("ldmatrix.sync.aligned.m8n8.x4.shared.b16 {%0,%1,%2,%3},[%4];" : "=r"(q[4]), "=r"(q[5]), "=r"(q[6]), "=r"(q[7]) : "r"(a ^ 32) : "memory");
}
template <int LO, int HI>
__device__ __forceinline__ void attn_exp(float (&S)[32], uint32_t (&P)[16], float& l0, float& l1) {
#pragma unroll
  for (int i = LO; i < HI; i++) {
    const float a = ex2(S[2 * i]), b = ex2(S[2 * i + 1]);
    if (i & 1) { l1 += a; l1 += b; } else { l0 += a; l0 += b; }
    P[i] = pack(a, b);
  }
}
__device__ __forceinline__ void sched_pin(float l0, float l1, uint32_t never) {
  asm volatile("{\n.reg .pred p;\nsetp.ne.u32 p,%3,0;\n@p st.shared.v2.f32 [%2],{%0,%1};\n}" ::"f"(l0), "f"(l1), "r"(SM_DUMMY), "r"(never) : "memory");
}
__device__ __forceinline__ void attn_finish(float (&O)[16], float l0, float l1, uint32_t blk, uint32_t bar) {
  l0 += __shfl_xor_sync(~0u, l0, 1); l1 += __shfl_xor_sync(~0u, l1, 1);
  l0 += __shfl_xor_sync(~0u, l0, 2); l1 += __shfl_xor_sync(~0u, l1, 2);
  const float i0 = rcp(l0), i1 = rcp(l1);
  const uint32_t t = threadIdx.x & 127, r = (t >> 5) * 16 + (t & 15);
  const uint32_t a = blk + r * 64 + (((((t >> 4) & 1)) ^ ((r >> 1) & 3)) << 4);
  stsm4(a, pack(O[0] * i0, O[1] * i0), pack(O[2] * i1, O[3] * i1), pack(O[4] * i0, O[5] * i0), pack(O[6] * i1, O[7] * i1));
  stsm4(a ^ 32, pack(O[8] * i0, O[9] * i0), pack(O[10] * i1, O[11] * i1), pack(O[12] * i0, O[13] * i0), pack(O[14] * i1, O[15] * i1));
  fence_async_smem();
  mbar_arrive(bar);
}

__global__ void __launch_bounds__(512, 1) fused_kernel(const __grid_constant__ Maps mp, int never) {
  extern __shared__ __align__(1024) char smem_raw[];
  if (threadIdx.x == 0) TLREC(0);
  const int warp = __shfl_sync(~0u, (int)(threadIdx.x >> 5), 0);
  const int lane = threadIdx.x & 31;
  const int j = (blockIdx.x & 3) + ((blockIdx.x >> 6) << 2), i = (blockIdx.x >> 2) & 15;
  const uint32_t hf = j >> 2;

  if (warp == 0) {
    if (elect_one()) {
      const CUtensorMap* wkv = (j & 2) ? &mp.wv : &mp.wk;
#pragma unroll
      for (int s = 0; s < 8; s++) mbar_init(B_HX + s * 8, 1);
#pragma unroll
      for (int s = 0; s < 3; s++) mbar_init(B_HW + s * 8, 1);
      asm volatile("fence.mbarrier_init.release.cluster;" ::: "memory");
      fence_async_smem();
      TLREC(60);
#pragma unroll
      for (uint32_t st = 0; st < EARLYST; st++) {
        mbar_expect(B_HX + st * 8, WKVLSU ? 16384 : 20480);
        tma3d(SB + st * 16384, &mp.xBh, 0, i * 128 + hf * 64, st * 2, B_HX + st * 8);
        if (!WKVLSU) tma2d(SM_KV + st * 4096, wkv, (j & 1) * 16, st * 128, B_HX + st * 8);
        if (HOLDQ == 2 && st >= WQ0 && st < WQ0 + 3) {
          mbar_expect(B_HW + (st - WQ0) * 8, 16384);
          tma2d(head_wq(st - WQ0), &mp.wqh, j * 128, (st - WQ0) * 128, B_HW + (st - WQ0) * 8);
        }
      }
    }
  } else if (warp == 1) {
    if (elect_one()) {
      if ((uint32_t)__cvta_generic_to_shared(smem_raw) != SB) __trap();
      prefetch_map(&mp.wqh);
      for (int s = 3; s < 8; s++) mbar_init(B_HW + s * 8, 1);
      for (int s = 0; s < 3; s++) mbar_init(B_HE + s * 8, HOLDQ == 1 ? 1 : 2);
      mbar_init(B_HD0, 1); mbar_init(B_HD1, 1); mbar_init(B_KINFO, 1); mbar_init(B_FLAGSET, 1);
      for (int s = 0; s < 4; s++) {
        mbar_init(B_FULL + s * 8, 1); mbar_init(B_EMPTY + s * 8, 1);
        mbar_init(B_KVFULL + s * 8, 1); mbar_init(B_KVEMPTY + s * 8, 2);
      }
      mbar_init(B_QRDY, 128); mbar_init(B_GPART, 128); mbar_init(B_GSTORE, 128);
      mbar_init(B_OSTORE, 128); mbar_init(B_OSTORE + 8, 128);
      asm volatile("fence.mbarrier_init.release.cluster;" ::: "memory");
      fence_async_smem();
    }
  }
  __syncthreads();
  if (threadIdx.x == 0) TLREC(39);

  if (warp < 4) {
    asm volatile("setmaxnreg.dec.sync.aligned.u32 %0;" ::"n"(REG_S));
    if (warp == 0) {
      if (elect_one()) {
        const CUtensorMap* wkv = (j & 2) ? &mp.wv : &mp.wk;
#pragma unroll
        for (uint32_t st = EARLYST; st < 8; st++) {
          mbar_expect(B_HX + st * 8, WKVLSU ? 16384 : 20480);
          tma3d(SB + st * 16384, &mp.xBh, 0, i * 128 + hf * 64, st * 2, B_HX + st * 8);
          if (!WKVLSU) tma2d(SM_KV + st * 4096, wkv, (j & 1) * 16, st * 128, B_HX + st * 8);
        }
#pragma unroll
        for (uint32_t w = 0; w < (HOLDQ == 2 ? 0 : 3); w++) {
          mbar_expect(B_HW + w * 8, 16384);
          tma2d(head_wq(w), &mp.wqh, j * 128, w * 128, B_HW + w * 8);
        }
        TLREC(61);
        prefetch_map(&mp.xB); prefetch_map(&mp.wq); prefetch_map(&mp.xA); prefetch_map(&mp.wqkv);
      }
      if (GATEWQ) mbar_wait(B_FLAGSET, 0);
#pragma unroll
      for (uint32_t e = 0; e < 3; e++) {
        mbar_wait(B_HE + e * 8, 0);
        if (elect_one()) {
#pragma unroll
          for (uint32_t w = (e == 0 ? 3 : 2 + 2 * e); w < 4 + 2 * e; w++) {
            mbar_expect(B_HW + w * 8, 16384);
            tma2d(head_wq(w), &mp.wqh, j * 128, w * 128, B_HW + w * 8);
          }
        }
      }
      mbar_wait(B_HD0, 0);
      if (GATE) mbar_wait(B_KINFO, 0);
#pragma unroll 1
      for (uint32_t t = 0; t < 4; t++) {
        const bool kvt = t == 1 || t == 2;
        const int c0 = kvt ? 1024 + (2 * j + t - 1) * 64 : j * 128, c1 = kvt ? c0 + 1024 : c0 + 64;
        const CUtensorMap* xm = t == 0 ? &mp.xB : &mp.xA;
        const CUtensorMap* wm = t == 0 ? &mp.wq : &mp.wqkv;
#pragma unroll 1
        for (uint32_t r = 0; r < 4; r++) {
#pragma unroll
          for (uint32_t s = 0; s < 4; s++) {
            const uint32_t f = B_FULL + s * 8, k = r * 256 + s * 64;
            mbar_wait(B_EMPTY + s * 8, (r & 1) ^ 1);
            if (elect_one()) {
              mbar_expect(f, 32768);
              tma2d(SM_X + s * 16384, xm, k, i * 128, f);
              tma2d(SM_W0 + s * 8192, wm, c0, k, f);
              tma2d(SM_W1 + s * 8192, wm, c1, k, f);
            }
          }
        }
      }
      mbar_wait(B_EMPTY, 1);
      cnt_wait(C_RED + j, 32);
      fence_async_gmem();
      if (elect_one()) {
        TLREC(20);
        mbar_expect(B_FULL, 16384);
        bulk_load(SM_X, g_blob + j * 4096, 16384, B_FULL);
      }
#pragma unroll 1
      for (int c = 0; c < 8; c++) {
        const int cnt = c < 4 ? C_OA + i : C_OB + i * 4 + max(c - 4, 1);
        const CUtensorMap* xm = c < 4 ? &mp.oaL : &mp.obL;
        bool ready = (c > 0 && c < 4) || c == 5;
        if (!ready) {
          ready = __shfl_sync(~0u, cnt_ld(cnt), 0) >= 8;
          fence_async_gmem();
        }
#pragma unroll
        for (int q = 0; q < 4; q++) {
          const uint32_t s = (q + 1) & 3, f = B_FULL + s * 8;
          mbar_wait(B_EMPTY + s * 8, ((q == 3 ? c + 1 : c) & 1) ^ 1);
          if (elect_one()) {
            mbar_expect(f, 32768);
            if (ready) tma2d(SM_X + s * 16384, xm, (c & 3) * 256 + q * 64, i * 128, f);
            if (c < 4) {
              tma2d(SM_W0 + s * 8192, &mp.woA, j * 128, c * 256 + q * 64, f);
              tma2d(SM_W1 + s * 8192, &mp.woA, j * 128 + 64, c * 256 + q * 64, f);
            } else {
              tma4d(SM_W0 + s * 8192, &mp.woB, j * 128, 0, c - 4, q * 2, f);
              tma4d(SM_W1 + s * 8192, &mp.woB, j * 128 + 64, 0, c - 4, q * 2, f);
            }
          }
          if (q >= 2 && !ready && (q == 3 || c < 7)) {
            cnt_wait(cnt, 8);
            fence_async_gmem();
            if (elect_one()) {
              TLREC(21 + c);
#pragma unroll
              for (int x = 0; x <= q; x++) tma2d(SM_X + ((x + 1) & 3) * 16384, xm, (c & 3) * 256 + x * 64, i * 128, B_FULL + ((x + 1) & 3) * 8);
            }
            ready = true;
          }
        }
      }
      uint32_t last = 0;
      if (elect_one()) asm volatile("atom.relaxed.gpu.global.add.u32 %0,[%1],1;" : "=r"(last) : "l"(cnt_ptr(C_DONE)) : "memory");
      if (__reduce_max_sync(~0u, last) == gridDim.x - 1) {
        fence_acquire();
        for (int k = lane; k < 128; k += 32) g_flags[F_KVB + k] = 0;
        for (int k = lane; k < C_NUM; k += 32) *cnt_ptr(k) = 0;
      }
    } else if (warp == 1) {
      if (elect_one()) { prefetch_map(&mp.kvS); prefetch_map(&mp.kvb); }
      uint4 a;
      uint32_t spins = 0, issued = 0;
      if (!EARLYPOLL) mbar_wait(B_HD1, 0);
      while (true) {
        const uint32_t* p = g_flags + F_KVB + lane * 4;
        asm volatile("ld.relaxed.gpu.global.v4.u32 {%0,%1,%2,%3},[%4];" : "=r"(a.x), "=r"(a.y), "=r"(a.z), "=r"(a.w) : "l"(p) : "memory");
        const uint32_t rdy = __ballot_sync(~0u, (a.x & a.y & a.z & a.w & 1u) != 0);
        if (EARLYPOLL && spins == 0) mbar_wait(B_HD1, 0);
        if (!issued && (rdy & (EARLYKV ? 15u : ~0u)) == (EARLYKV ? 15u : ~0u)) {
          issued = 1;
          fence_acquire();
          fence_async_gmem();
          if (elect_one()) {
            mbar_expect(B_KVFULL, 16384);
            tma2d(SM_KV, &mp.kvb, 0, 0, B_KVFULL);
            mbar_expect(B_KVFULL + 8, 16384);
            tma2d(SM_KV + 16384, &mp.kvb, 0, 128, B_KVFULL + 8);
          }
        }
        if (rdy == ~0u) break;
        __nanosleep(POLLNS);
        SPIN_FAIL(spins, 999)
      }
      fence_acquire();
      fence_async_gmem();
      const uint32_t knm = __reduce_max_sync(~0u, __float_as_uint(__uint_as_float(a.x) + __uint_as_float(a.y)));
      const uint32_t vnm = __reduce_max_sync(~0u, max(a.z, a.w));
      if (elect_one()) {
        TLREC(8);
        const float vn = __uint_as_float(vnm);
        const bool vok = vn <= 1.2089258e24f   && vn >= 8.2718061e-25f  ;
        asm volatile("st.shared.u32 [%0],%1;" ::"r"(SM_KINFO), "r"(vok ? knm : 0x7f800000u) : "memory");
        mbar_arrive(B_KINFO);
      }
      mbar_wait(B_HD0, 0);
#pragma unroll 1
      for (uint32_t b = 0; b < 16; b++) {
#pragma unroll
        for (uint32_t s = 0; s < 4; s++) {
          if (s >= 2 || b > 0) {
            mbar_wait(B_KVEMPTY + s * 8, (b & 1) ^ 1);
            if (elect_one()) {
              mbar_expect(B_KVFULL + s * 8, 16384);
              tma2d(SM_KV + s * 16384, &mp.kvb, 0, (b & 3) * 512 + s * 128, B_KVFULL + s * 8);
            }
          }
        }
      }
    } else if (warp == 2) {
      if (elect_one()) {
        prefetch_map(&mp.obS);
#pragma unroll 1
        for (int p = 0; p < 4; p++) {
          const int h0 = p < 2 ? 0 : p, h1 = p < 2 ? 1 : p;
          const int r0 = p < 2 ? (hf ^ p) : 0, r1 = p < 2 ? (hf ^ p) : 1;
          mbar_wait(B_OSTORE, p & 1);
          tma_store2d(&mp.obS, h0 * 256 + j * 32, i * 128 + r0 * 64, SM_Q + (3 - p) * 8192);
          mbar_wait(B_OSTORE + 8, p & 1);
          tma_store2d(&mp.obS, h1 * 256 + j * 32, i * 128 + r1 * 64, SM_Q + (3 - p) * 8192 + 4096);
          bulk_commit();
          if (p > 0) {
            bulk_wait_all();
            cnt_add(C_OB + i * 4 + p);
          }
          TLREC(32 + p);
        }
      }
    } else {
#pragma unroll 1
      for (int t = 0; t < 2; t++) {
        const int hp = 2 * j + t;
        mbar_wait(B_GPART, t);
        if (lane == 0) {
          cnt_add(C_PART + hp);
          cnt_wait(C_PART + hp, 16);
        }
        __syncwarp();
        fence_acquire();
        const float* zp = g_zpart + (hp * 16 + (lane >> 2)) * 64 + 4 * i + (lane & 3);
        float z = __ldcg(zp) + __ldcg(zp + 8 * 64);
        const float4* pp = g_part + hp * 16 * 512 + i * 32 + lane;
        float4 acc = make_float4(0.f, 0.f, 0.f, 0.f);
#pragma unroll 1
        for (int r = 0; r < 16; r += 4) {
          const float4 v0 = __ldcg(pp + (r + 0) * 512), v1 = __ldcg(pp + (r + 1) * 512), v2 = __ldcg(pp + (r + 2) * 512), v3 = __ldcg(pp + (r + 3) * 512);
          acc.x += (v0.x + v1.x) + (v2.x + v3.x); acc.y += (v0.y + v1.y) + (v2.y + v3.y);
          acc.z += (v0.z + v1.z) + (v2.z + v3.z); acc.w += (v0.w + v1.w) + (v2.w + v3.w);
        }
        z += __shfl_xor_sync(~0u, z, 4); z += __shfl_xor_sync(~0u, z, 8); z += __shfl_xor_sync(~0u, z, 16);
        uint32_t* blob = g_blob + j * 4096 + t * 2048;
        const int q = i >> 2, d0 = (i & 3) * 16 + (lane >> 2);
        uint32_t* bp = blob + d0 * 32 + ((q ^ (d0 & 7)) << 2) + (lane & 3);
        bp[0] = pack(acc.x, acc.y);
        bp[8 * 32] = pack(acc.z, acc.w);
        if (lane < 4) {
          const int d = 4 * i + lane;
          const uint32_t zz = pack(z, z);
          *(uint4*)(blob + d * 32 + ((4 ^ (d & 7)) << 2)) = make_uint4(zz, zz, zz, zz);
        }
        fence_async_gmem();
        __syncwarp();
        if (lane == 0) { cnt_add(C_RED + j); TLREC(18 + t); }
      }
      if (elect_one()) {
        prefetch_map(&mp.oaS); prefetch_map(&mp.out);
#pragma unroll 1
        for (int e = 0; e < 2; e++) {
          const uint32_t s = e == 0 ? 3 : 0;
          const CUtensorMap* m = e == 0 ? &mp.oaS : &mp.out;
          mbar_wait(B_GSTORE, e);
          tma_store2d(m, j * 128, i * 128, SM_X + s * 16384);
          tma_store2d(m, j * 128 + 64, i * 128, SM_X + s * 16384 + 8192);
          tma_store2d(m, j * 128, i * 128 + 64, SM_W0 + s * 8192);
          tma_store2d(m, j * 128 + 64, i * 128 + 64, SM_W1 + s * 8192);
          bulk_commit();
          bulk_wait_read();
          mbar_arrive(B_EMPTY + s * 8);
          if (e == 0) { bulk_wait_all(); cnt_add(C_OA + i); }
          TLREC(36 + e);
        }
      }
    }
  } else if (warp < 8) {
    asm volatile("setmaxnreg.inc.sync.aligned.u32 %0;" ::"n"(REG_G));
    const uint32_t tid = threadIdx.x & 127;
    const bool leader = tid == 0;
    const uint32_t sts = ((tid >> 5) * 16 + (tid & 15)) * 128 + ((((tid >> 4) & 1) ^ (tid & 7)) << 4);
    {
      float a0[64], a1[32];
      mbar_wait(B_FULL, 0);
      TLREC0(10);
      qb_stage<true>(a0, a1, 0, hf, true, leader);
#pragma unroll 1
      for (uint32_t n = 1; n < 16; n++) qb_stage<false>(a0, a1, n, hf, n < 15, leader);
      wg_wait<0>();
      pin(a0); pin(a1);
      mbar_arrive_if(B_EMPTY + 3 * 8, leader);
      TLREC0(46);
      const uint32_t r = (tid >> 5) * 16 + (tid & 15);
      const uint32_t qa = SM_Q + r * 64 + ((((tid >> 4) & 1) ^ ((r >> 1) & 3)) << 4);
      uint32_t qm = q_block(a0, qa + 4 * 4096, 0);
      qm = q_block(a0 + 16, qa + 5 * 4096, qm);
      qm = q_block(a0 + 32, qa + (3 - hf) * 4096, qm);
      qm = q_block(a0 + 48, qa + (1 - hf) * 4096, qm);
      qm = q_block(a1, qa + (2 + hf) * 4096, qm);
      qm = q_block(a1 + 16, qa + hf * 4096, qm);
      fence_async_smem();
      mbar_wait(B_KINFO, 0);
      const uint32_t unsafe = wg_any(bound_exceeded(qm));
      if (leader) asm volatile("st.shared.u32 [%0],%1;" ::"r"(SM_UNSAFE), "r"(unsafe) : "memory");
      mbar_arrive(B_QRDY);
      TLREC0(47);
    }
#pragma unroll 1
    for (int t = 0; t < 2; t++) {
      float a0[64], a1[64];
      gemm_tile<true>(a0, a1, 16 + t * 16, leader);
      TLREC0(11 + 2 * t);
      bar_sync(1);
      const uint32_t xs = SM_X + 3 * 16384;
#pragma unroll
      for (int g = 0; g < 8; g++)
        stsm4(xs + (g >> 2) * 8192 + (sts ^ ((g & 3) << 5)), pack(a1[8 * g], a1[8 * g + 1]), pack(a1[8 * g + 2], a1[8 * g + 3]),
              pack(a1[8 * g + 4], a1[8 * g + 5]), pack(a1[8 * g + 6], a1[8 * g + 7]));
      fence_async_smem();
      uint32_t p[32];
      float z0 = 0.f, z1 = 0.f;
#pragma unroll
      for (int g = 0; g < 16; g++) {
        const float a = phi(a0[4 * g]), b = phi(a0[4 * g + 1]), c = phi(a0[4 * g + 2]), d = phi(a0[4 * g + 3]);
        z0 += a + b; z1 += c + d;
        p[2 * g] = pack(a, b); p[2 * g + 1] = pack(c, d);
      }
      pin(p);
      bar_sync(1);
      float D[32];
      wg_fence();
      wgmma_rs_n64_z<0>(D, p[0], p[1], p[2], p[3], descK(xs >> 4));
#pragma unroll
      for (int kk = 1; kk < 8; kk++)
        wgmma_rs_n64<0>(D, p[4 * kk], p[4 * kk + 1], p[4 * kk + 2], p[4 * kk + 3], descK((xs >> 4) + (kk >> 2) * 512 + (kk & 3) * 2), 1);
      wg_commit();
      z0 += __shfl_xor_sync(~0u, z0, 1); z1 += __shfl_xor_sync(~0u, z1, 1);
      z0 += __shfl_xor_sync(~0u, z0, 2); z1 += __shfl_xor_sync(~0u, z1, 2);
      const int slot = (2 * j + t) * 16 + i;
      if ((tid & 3) == 0) {
        float* zp = g_zpart + slot * 64 + (tid >> 5) * 16 + ((tid & 31) >> 2);
        zp[0] = z0; zp[8] = z1;
      }
      wg_wait<0>();
      pin(D);
      mbar_arrive_if(B_EMPTY + 3 * 8, leader);
      const bool hi = tid >= 64;
      float4* pp = g_part + slot * 512 + tid;
#pragma unroll
      for (int q = 0; q < 4; q++)
        pp[q * 128] = make_float4(hi ? D[16 + 4 * q] : D[4 * q], hi ? D[17 + 4 * q] : D[4 * q + 1], hi ? D[18 + 4 * q] : D[4 * q + 2], hi ? D[19 + 4 * q] : D[4 * q + 3]);
      mbar_arrive(B_GPART);
      TLREC0(12 + 2 * t);
    }
    {
      float a0[64], a1[64];
      gemm_tile<false>(a0, a1, 48, leader);
      TLREC0(15);
      uint32_t p0[32], p1[32];
#pragma unroll
      for (int g = 0; g < 32; g++) p0[g] = pack(phi(a0[2 * g]), phi(a0[2 * g + 1]));
#pragma unroll
      for (int g = 0; g < 32; g++) p1[g] = pack(phi(a1[2 * g]), phi(a1[2 * g + 1]));
      pin(p0); pin(p1);
      bar_sync(1);
      mbar_wait(B_FULL, 0);
      TLREC0(16);
#pragma unroll
      for (int r = 0; r < 4; r++) {
        uint32_t(&p)[32] = (r < 2) ? p0 : p1;
        const int h = (r & 1) * 2;
        const uint32_t kv = (SM_X >> 4) + h * 256;
        float D0[20], D1[20];
        wg_fence();
        wgmma_rs_n40_z<1>(D0, p[8 * h], p[8 * h + 1], p[8 * h + 2], p[8 * h + 3], descMN(kv));
        wgmma_rs_n40_z<1>(D1, p[8 * h + 8], p[8 * h + 9], p[8 * h + 10], p[8 * h + 11], descMN(kv + 256));
        wgmma_rs_n40<1>(D0, p[8 * h + 4], p[8 * h + 5], p[8 * h + 6], p[8 * h + 7], descMN(kv + 128), 1);
        wgmma_rs_n40<1>(D1, p[8 * h + 12], p[8 * h + 13], p[8 * h + 14], p[8 * h + 15], descMN(kv + 256 + 128), 1);
        wg_commit();
        wg_wait<0>();
        pin(D0); pin(D1);
        const uint32_t dst = r == 0 ? SM_X + 3 * 16384 : r == 1 ? SM_X + 3 * 16384 + 8192 : r == 2 ? SM_W0 + 3 * 8192 : SM_W1 + 3 * 8192;
        const float i0 = rcp(D0[16] + 1e-6f), i1 = rcp(D0[18] + 1e-6f), i2 = rcp(D1[16] + 1e-6f), i3 = rcp(D1[18] + 1e-6f);
#pragma unroll
        for (int g = 0; g < 2; g++) {
          stsm4(dst + (sts ^ (g << 5)), pack(D0[8 * g] * i0, D0[8 * g + 1] * i0), pack(D0[8 * g + 2] * i1, D0[8 * g + 3] * i1),
                pack(D0[8 * g + 4] * i0, D0[8 * g + 5] * i0), pack(D0[8 * g + 6] * i1, D0[8 * g + 7] * i1));
          stsm4(dst + (sts ^ ((g + 2) << 5)), pack(D1[8 * g] * i2, D1[8 * g + 1] * i2), pack(D1[8 * g + 2] * i3, D1[8 * g + 3] * i3),
                pack(D1[8 * g + 4] * i2, D1[8 * g + 5] * i2), pack(D1[8 * g + 6] * i3, D1[8 * g + 7] * i3));
        }
      }
      mbar_arrive_if(B_EMPTY, leader);
      fence_async_smem();
      mbar_arrive(B_GSTORE);
      TLREC0(17);
    }
    float a0[64], a1[64];
#pragma unroll 1
    for (int t = 0;; t++) {
      gemm_tile<false>(a0, a1, 65 + t * 16, leader, t == 0 ? 16 : 12);
      if (t == 1) break;
      TLREC0(40);
      bar_sync(1);
#pragma unroll
      for (int g = 0; g < 8; g++)
        stsm4(SM_X + (g >> 2) * 8192 + (sts ^ ((g & 3) << 5)), pack(a0[8 * g], a0[8 * g + 1]), pack(a0[8 * g + 2], a0[8 * g + 3]),
              pack(a0[8 * g + 4], a0[8 * g + 5]), pack(a0[8 * g + 6], a0[8 * g + 7]));
#pragma unroll
      for (int g = 0; g < 8; g++)
        stsm4(SM_W0 + (g >> 2) * 32768 + (sts ^ ((g & 3) << 5)), pack(a1[8 * g], a1[8 * g + 1]), pack(a1[8 * g + 2], a1[8 * g + 3]),
              pack(a1[8 * g + 4], a1[8 * g + 5]), pack(a1[8 * g + 6], a1[8 * g + 7]));
      fence_async_smem();
      mbar_arrive(B_GSTORE);
      TLREC0(41);
    }
    TLREC0(49);
    mbar_arrive_if(B_EMPTY, leader);
    float h0[32], h1[32], h2[32], h3[32];
    const float one = __int_as_float(0x3f800000 + never);
#pragma unroll
    for (int e = 0; e < 32; e++) { h0[e] = a0[e] * one; h1[e] = a0[32 + e] * one; h2[e] = a1[e] * one; h3[e] = a1[32 + e] * one; }
    pin(h0); pin(h1); pin(h2); pin(h3);
#pragma unroll
    for (int q = 0; q < 4; q++) {
      mbar_wait(B_FULL + ((q + 1) & 3) * 8, q < 3 ? 1 : 0);
      wg_fence();
      final_mma<0>(h0, 4 * q, 4 * q + 4);
    }
    wg_commit();
    final_mma<1>(h1, 0, 6);  wg_commit(); wg_wait<1>(); final_store<0>(h0, sts, &mp.out, i, j, warp == 4);
    wg_fence(); final_mma<1>(h1, 6, 16); wg_commit();
    final_mma<2>(h2, 0, 6);  wg_commit(); wg_wait<1>(); final_store<1>(h1, sts, &mp.out, i, j, warp == 4);
    wg_fence(); final_mma<2>(h2, 6, 16); wg_commit();
    final_mma<3>(h3, 0, 6);  wg_commit(); wg_wait<1>(); final_store<2>(h2, sts, &mp.out, i, j, warp == 4);
    wg_fence(); final_mma<3>(h3, 6, 16); wg_commit(); wg_wait<0>();
    TLREC0(42);
    final_store<3>(h3, sts, &mp.out, i, j, warp == 4);
    TLREC0(43);
    if (warp == 4) {
      bulk_wait_read();
      TLREC0(38);
    }
  } else {
    asm volatile("setmaxnreg.inc.sync.aligned.u32 %0;" ::"n"(REG_A));
    const uint32_t a = (warp >> 2) - 2;
    const uint32_t tid = threadIdx.x & 127;
    const bool leader = tid == 0;
    uint32_t qm = 0;
    if (a == 0) {
      float acc[32];
#pragma unroll
      for (int e = 0; e < 32; e++) acc[e] = 0.f;
      pin(acc);
#pragma unroll
      for (uint32_t st = 0; st < 8; st++) {
        const uint32_t x = (SB >> 4) + st * 1024, w = head_wq(st) >> 4;
        if ((HOLDQ == 1 && st == 0) || (HOLDQ == 2 && st == 3)) mbar_wait(LATEQ ? B_FLAGSET : B_HD1, 0);
        if (!HOLDQ || (HOLDQ == 2 && st < 3)) mbar_wait(B_HX + st * 8, 0);
        mbar_wait(B_HW + st * 8, 0);
        if (st == 0) TLREC0(50);
        wg_fence();
#pragma unroll
        for (int kk = 0; kk < 8; kk++) wgmma_ss_n64<0, 1>(acc, descK(x + (kk >> 2) * 512 + (kk & 3) * 2), descMN(w + kk * 128), 1);
        wg_commit();
        if (st < 3) {
          wg_wait<0>();
          mbar_arrive_if(B_HE + st * 8, leader);
        }
      }
      wg_wait<0>();
      pin(acc);
      mbar_arrive_if(B_HD0, leader);
      TLREC0(51);
      const uint32_t r = (tid >> 5) * 16 + (tid & 15);
      const uint32_t qa = SM_Q + 6 * 4096 + r * 64 + ((((tid >> 4) & 1) ^ ((r >> 1) & 3)) << 4);
      qm = q_block(acc, qa, 0);
      qm = q_block(acc + 16, qa + 4096, qm);
      qm = __reduce_max_sync(~0u, qm);
      if (lane == 0) asm volatile("st.shared.u32 [%0],%1;" ::"r"(SM_WMAX + 16 + (tid >> 5) * 4), "r"(qm) : "memory");
      fence_async_smem();
    } else {
      float acc[8];
      uint32_t* flagp = g_flags + F_KVB + (i * 2 + hf) * 4 + (j & 3);
      asm volatile("" : "+l"(flagp));
#pragma unroll
      for (int e = 0; e < 8; e++) acc[e] = 0.f;
      pin(acc);
#pragma unroll 1
      for (uint32_t st = 0; st < 8; st++) {
        const uint32_t x = (SB >> 4) + st * 1024, w = (SM_KV >> 4) + st * 256;
        mbar_wait(B_HX + st * 8, 0);
        if (st == 0) TLREC0(1);
        if (st == 7) TLREC0(48);
        wg_fence();
#pragma unroll
        for (int kk = 0; kk < 8; kk++) wgmma_ss_n16<0, 1>(acc, descK(x + (kk >> 2) * 512 + (kk & 3) * 2), mkdesc(w + kk * 32, 16, 256, 3), 1);
        wg_commit();
        if (!HOLDQ || (HOLDQ == 2 && st < 3)) {
          wg_wait<0>();
          mbar_arrive_if(B_HE + st * 8, leader && st < 3);
        }
      }
      wg_wait<0>();
      pin(acc);
      mbar_arrive_if(B_HD1, leader);
      TLREC0(2);
      const uint32_t stg = SM_Q + 4 * 4096;
      stsm4(stg + ((tid >> 5) * 16 + (tid & 15)) * 32 + ((tid >> 4) & 1) * 16, pack(acc[0], acc[1]), pack(acc[2], acc[3]), pack(acc[4], acc[5]), pack(acc[6], acc[7]));
      fence_async_smem();
      float n0 = acc[0] * acc[0] + acc[1] * acc[1] + acc[4] * acc[4] + acc[5] * acc[5];
      float n1 = acc[2] * acc[2] + acc[3] * acc[3] + acc[6] * acc[6] + acc[7] * acc[7];
      n0 += __shfl_xor_sync(~0u, n0, 1); n1 += __shfl_xor_sync(~0u, n1, 1);
      n0 += __shfl_xor_sync(~0u, n0, 2); n1 += __shfl_xor_sync(~0u, n1, 2);
      const uint32_t wm = __reduce_max_sync(~0u, max(__float_as_uint(n0), __float_as_uint(n1)));
      if (lane == 0) asm volatile("st.shared.u32 [%0],%1;" ::"r"(SM_WMAX + (tid >> 5) * 4), "r"(wm) : "memory");
      bar_sync(3);
      if (leader) {
        tma_store2d(&mp.kvS, (j & 3) * 16, i * 128 + hf * 64, stg);
        bulk_commit();
        uint4 v;
        asm volatile("ld.shared.v4.u32 {%0,%1,%2,%3},[%4];" : "=r"(v.x), "=r"(v.y), "=r"(v.z), "=r"(v.w) : "r"(SM_WMAX) : "memory");
        const uint32_t m = max(max(v.x, v.y), max(v.z, v.w)) | 1u;
        bulk_wait_all();
        if (LATEQ == 1) mbar_arrive(B_FLAGSET);
        asm volatile("st.release.gpu.global.u32 [%0],%1;" ::"l"(flagp), "r"(m) : "memory");
        if (GATEWQ || LATEQ == 2) mbar_arrive(B_FLAGSET);
        TLREC(3);
      }
      __syncwarp();
    }
    asm volatile("bar.sync 2,256;" ::: "memory");
    {
      uint4 v;
      asm volatile("ld.shared.v4.u32 {%0,%1,%2,%3},[%4];" : "=r"(v.x), "=r"(v.y), "=r"(v.z), "=r"(v.w) : "r"(SM_WMAX + 16) : "memory");
      qm = max(max(v.x, v.y), max(v.z, v.w));
    }
    const uint32_t qtop = (SM_Q >> 4) + (6 + a) * 256, kv16 = SM_KV >> 4, obar = B_OSTORE + a * 8;
    float O[16], S0[32];
    uint32_t pass = 0;
    mbar_wait(B_KVFULL, 0);
    if (a == 0) TLREC0(4);
    wg_fence();
    wgmma_ss_n64_z<0, 0>(S0, descK64(qtop), descK(kv16));
    wgmma_ss_n64<0, 0>(S0, descK64(qtop + 2), descK(kv16 + 2), 1);
    wg_commit();
    wg_wait<0>();
    pin(S0);
    mbar_wait(B_KINFO, 0);
    if (__shfl_sync(~0u, (uint32_t)bound_exceeded(qm), 0) == 0) {
      float S1[32];
      uint32_t P0[16], P1[16];
      float l0 = 0.f, l1 = 0.f, lp0 = 0.f, lp1 = 0.f;
#pragma unroll
      for (int e = 0; e < 16; e++) { O[e] = 0.f; P1[e] = 0; }
#pragma unroll
      for (int e = 0; e < 32; e++) S1[e] = 0.f;
      pin(O); pin(P1); pin(S1);
      uint32_t bend = 16;
      if (a == 0) TLREC0(29);
      uint32_t q[8];
      const uint32_t qoff = ((tid >> 5) * 16 + (tid & 15)) * 64 + ((((tid >> 4) & 1) ^ ((tid >> 1) & 3)) << 4);
      load_q(q, (qtop << 4) + qoff);
#pragma unroll 1
      for (uint32_t b = 0; b < bend; b++) {
        if (a == 0 && b == 1) TLREC0(30);
        if (a == 0 && b == 2) TLREC0(31);
        const bool first = (b & 3) == 0;
        const uint32_t qc = qtop - (b >> 2) * 512, qn = qtop - (((b + 1) >> 2) & 3) * 512;
#pragma unroll
        for (int u = 0; u < 4; u++) {
          const uint32_t cur = kv16 + u * 1024, prv = kv16 + ((u + 3) & 3) * 1024, nxt = kv16 + ((u + 1) & 3) * 1024;
          attn_exp<16 - TAIL, 16>(S1, P1, l0, l1);
          pin(P1);
          if (u == 0) { lp0 = first ? l0 : lp0; lp1 = first ? l1 : lp1; l0 = first ? 0.f : l0; l1 = first ? 0.f : l1; }
          attn_batch_rs(S1, q, cur + 512, O, P1, prv + 512, 1);
          const uint32_t ok = mbar_test(B_KVFULL + ((u + 1) & 3) * 8, (u == 3 ? b + 1 : b) & 1);
          attn_exp<0, 16 - TAIL - PINAT>(S0, P0, l0, l1);
          sched_pin(l0, l1, never);
          attn_exp<16 - TAIL - PINAT, 16 - TAIL>(S0, P0, l0, l1);
          wg_wait<0>();
          pin(S1); pin(O);
          mbar_arrive_if(B_KVEMPTY + ((u + 3) & 3) * 8, leader && (u > 0 || b > 0));
          if (u == 0 && first && b > 0) {
            attn_finish(O, lp0, lp1, (qc + 512) << 4, obar);
            if (a == 0) TLREC0(4 + (b >> 2));
          }
          if (u == 3 && b == 3) {
            uint32_t us;
            mbar_wait(B_QRDY, 0);
            asm volatile("ld.shared.u32 %0,[%1];" : "=r"(us) : "r"(SM_UNSAFE) : "memory");
            if (__shfl_sync(~0u, us, 0)) bend = 4;
          }
          if (__builtin_expect(!ok, 0)) {
            if (u < 3 || b < 15) mbar_wait(B_KVFULL + ((u + 1) & 3) * 8, (u == 3 ? b + 1 : b) & 1);
          }
          if (u == 3) load_q(q, (qn << 4) + qoff);
          attn_exp<16 - TAIL, 16>(S0, P0, l0, l1);
          pin(P0);
          attn_batch_rs(S0, q, nxt, O, P0, cur, u == 0 ? !first : 1);
          attn_exp<0, 16 - TAIL - PINAT>(S1, P1, l0, l1);
          sched_pin(l0, l1, never);
          attn_exp<16 - TAIL - PINAT, 16 - TAIL>(S1, P1, l0, l1);
          wg_wait<0>();
          pin(S0); pin(O);
        }
      }
      attn_exp<16 - TAIL, 16>(S1, P1, l0, l1);
      pin(P1);
      wg_fence();
#pragma unroll
      for (int kk = 0; kk < 4; kk++)
        wgmma_rs_n32<1>(O, P1[4 * kk], P1[4 * kk + 1], P1[4 * kk + 2], P1[4 * kk + 3], descMN(kv16 + 3 * 1024 + 512 + 4 + kk * 128), 1);
      wg_commit();
      wg_wait<0>();
      pin(O);
      mbar_arrive_if(B_KVEMPTY + 3 * 8, leader);
      pass = bend >> 2;
      attn_finish(O, l0, l1, (qtop - (pass - 1) * 512) << 4, obar);
      TLREC0(44 + a);
    }
#pragma unroll 1
    for (; pass < 4; pass++) {
      float m0 = -INFINITY, m1 = -INFINITY, l0 = 0.f, l1 = 0.f;
      const uint32_t qc = qtop - pass * 512;
      if (pass == 1) mbar_wait(B_QRDY, 0);
#pragma unroll
      for (int e = 0; e < 16; e++) O[e] = 0.f;
#pragma unroll 1
      for (uint32_t b = 0; b < 32; b++) {
        const uint32_t g = pass * 16 + (b >> 1), kb = kv16 + (g & 3) * 1024 + (b & 1) * 512;
        if ((b & 1) == 0) mbar_wait(B_KVFULL + (g & 3) * 8, (g >> 2) & 1);
        float S[32];
        uint32_t P[16];
        wg_fence();
        wgmma_ss_n64_z<0, 0>(S, descK64(qc), descK(kb));
        wgmma_ss_n64<0, 0>(S, descK64(qc + 2), descK(kb + 2), 1);
        wg_commit();
        wg_wait<0>();
        pin(S);
        float x0 = m0, x1 = m1;
#pragma unroll
        for (int e = 0; e < 8; e++) {
          x0 = fmaxf(x0, fmaxf(S[4 * e], S[4 * e + 1]));
          x1 = fmaxf(x1, fmaxf(S[4 * e + 2], S[4 * e + 3]));
        }
        x0 = fmaxf(x0, __shfl_xor_sync(~0u, x0, 1)); x1 = fmaxf(x1, __shfl_xor_sync(~0u, x1, 1));
        x0 = fmaxf(x0, __shfl_xor_sync(~0u, x0, 2)); x1 = fmaxf(x1, __shfl_xor_sync(~0u, x1, 2));
        const float y0 = x0 == -INFINITY ? 0.f : x0, y1 = x1 == -INFINITY ? 0.f : x1;
        const float al0 = ex2(m0 - y0), al1 = ex2(m1 - y1);
        m0 = x0; m1 = x1;
        l0 *= al0; l1 *= al1;
#pragma unroll
        for (int e = 0; e < 8; e++) {
          const float pa = ex2(S[4 * e] - y0), pb = ex2(S[4 * e + 1] - y0), pc = ex2(S[4 * e + 2] - y1), pd = ex2(S[4 * e + 3] - y1);
          l0 += pa + pb; l1 += pc + pd;
          P[2 * e] = pack(pa, pb); P[2 * e + 1] = pack(pc, pd);
        }
#pragma unroll
        for (int e = 0; e < 4; e++) { O[4 * e] *= al0; O[4 * e + 1] *= al0; O[4 * e + 2] *= al1; O[4 * e + 3] *= al1; }
        pin(P); pin(O);
        wg_fence();
#pragma unroll
        for (int kk = 0; kk < 4; kk++) wgmma_rs_n32<1>(O, P[4 * kk], P[4 * kk + 1], P[4 * kk + 2], P[4 * kk + 3], descMN(kb + 4 + kk * 128), 1);
        wg_commit();
        wg_wait<0>();
        pin(O);
        mbar_arrive_if(B_KVEMPTY + (g & 3) * 8, leader && (b & 1));
      }
      attn_finish(O, l0, l1, qc << 4, obar);
    }
  }
}

typedef CUresult (*EncodeFn)(CUtensorMap*, CUtensorMapDataType, cuuint32_t, void*, const cuuint64_t*, const cuuint64_t*, const cuuint32_t*,
                             const cuuint32_t*, CUtensorMapInterleave, CUtensorMapSwizzle, CUtensorMapL2promotion, CUtensorMapFloatOOBfill);

void map2d(EncodeFn enc, CUtensorMap* m, const void* p, uint64_t cols, uint64_t rows, uint32_t bc, uint32_t br,
           CUtensorMapSwizzle sw = CU_TENSOR_MAP_SWIZZLE_128B) {
  cuuint64_t gd[2] = {cols, rows}, gs[1] = {cols * 2};
  cuuint32_t bd[2] = {bc, br}, es[2] = {1, 1};
  CUresult r = enc(m, CU_TENSOR_MAP_DATA_TYPE_BFLOAT16, 2, (void*)p, gd, gs, bd, es, CU_TENSOR_MAP_INTERLEAVE_NONE, sw,
      CU_TENSOR_MAP_L2_PROMOTION_L2_128B, CU_TENSOR_MAP_FLOAT_OOB_FILL_NONE);
  (void)r;
}

}

extern "C" void kernel_launch(void* const* d_in, const int* in_sizes, int n_in, void* d_out, int out_size) {
  (void)in_sizes; (void)n_in; (void)out_size;
  EncodeFn enc = nullptr;
  cudaDriverEntryPointQueryResult qr;
  cudaGetDriverEntryPoint("cuTensorMapEncodeTiled", (void**)&enc, cudaEnableDefault, &qr);
  void *kvb, *oa, *ob;
  cudaGetSymbolAddress(&kvb, g_small);
  kvb = ((Small*)kvb)->kvb;
  cudaGetSymbolAddress(&oa, g_oa);
  cudaGetSymbolAddress(&ob, g_ob);
  Maps mp;
  for (int k = 0; k < 8; k++) mp.in[k] = (const char*)d_in[k];
  map2d(enc, &mp.xA, d_in[0], 1024, 2048, 64, 128);
  map2d(enc, &mp.wqkv, d_in[1], 3072, 1024, 64, 64);
  map2d(enc, &mp.woA, d_in[2], 1024, 1024, 64, 64);
  map2d(enc, &mp.xB, d_in[3], 1024, 2048, 64, 128);
  map2d(enc, &mp.wq, d_in[4], 1024, 1024, 64, 64);
  map2d(enc, &mp.wk, d_in[5], 32, 1024, 16, 128, CU_TENSOR_MAP_SWIZZLE_32B);
  map2d(enc, &mp.wv, d_in[6], 32, 1024, 16, 128, CU_TENSOR_MAP_SWIZZLE_32B);
  map2d(enc, &mp.wqh, d_in[4], 1024, 1024, 64, 128);
  map2d(enc, &mp.kvS, kvb, 64, 2048, 16, 64, CU_TENSOR_MAP_SWIZZLE_NONE);
  {
    cuuint64_t gd[3] = {64, 2048, 16}, gs[2] = {2048, 128};
    cuuint32_t bd[3] = {64, 64, 2}, es[3] = {1, 1, 1};
    enc(&mp.xBh, CU_TENSOR_MAP_DATA_TYPE_BFLOAT16, 3, d_in[3], gd, gs, bd, es, CU_TENSOR_MAP_INTERLEAVE_NONE, CU_TENSOR_MAP_SWIZZLE_128B,
        HPROMO, CU_TENSOR_MAP_FLOAT_OOB_FILL_NONE);
  }
  {
    cuuint64_t gd[4] = {1024, 32, 4, 8}, gs[3] = {2048, 32 * 2048, 128 * 2048};
    cuuint32_t bd[4] = {64, 32, 1, 2}, es[4] = {1, 1, 1, 1};
    enc(&mp.woB, CU_TENSOR_MAP_DATA_TYPE_BFLOAT16, 4, d_in[7], gd, gs, bd, es, CU_TENSOR_MAP_INTERLEAVE_NONE, CU_TENSOR_MAP_SWIZZLE_128B,
        CU_TENSOR_MAP_L2_PROMOTION_L2_128B, CU_TENSOR_MAP_FLOAT_OOB_FILL_NONE);
  }
  map2d(enc, &mp.kvb, kvb, 64, 2048, 64, 128);
  map2d(enc, &mp.oaL, oa, 1024, 2048, 64, 128);
  map2d(enc, &mp.oaS, oa, 1024, 2048, 64, 64);
  map2d(enc, &mp.obL, ob, 1024, 2048, 64, 128);
  map2d(enc, &mp.obS, ob, 1024, 2048, 32, 64, CU_TENSOR_MAP_SWIZZLE_64B);
  map2d(enc, &mp.out, d_out, 2048, 2048, 64, 64);
  cudaFuncSetAttribute(fused_kernel, cudaFuncAttributeMaxDynamicSharedMemorySize, SMEM_BYTES);
  fused_kernel<<<128, 512, SMEM_BYTES, cudaStreamPerThread>>>(mp, 0);
}
```

```cpp
#include <cuda_runtime.h>
#include <cuda_bf16.h>
#include <cuda.h>
#include <stdint.h>

#define UNR 4
#define PINAT 3
#define FUNR 1
#define WPOS 0
#define QPOS 1
#define GENERAL_INLINE __noinline__
#define WQPF 3
#define ROLEMAP 0x3210
#define ORD 2
#define PACE 0
#define QBW 0
#define POLLNS 100
#define STNS 300
#define REG_S 40
#define REG_G 168
#define REG_A 152

namespace {

template<int TB> __device__ __forceinline__ void wgmma_rs_n32(float (&d)[16], uint32_t a0, uint32_t a1, uint32_t a2, uint32_t a3, uint64_t db, int sc){
  asm volatile("{\n.reg .pred p;\nsetp.ne.b32 p, %21, 0;\n"
  "wgmma.mma_async.sync.aligned.m64n32k16.f32.bf16.bf16 {%0,%1,%2,%3,%4,%5,%6,%7,%8,%9,%10,%11,%12,%13,%14,%15}, {%16,%17,%18,%19}, %20, p, 1, 1, %22;\n}\n"
  : "+f"(d[0]),"+f"(d[1]),"+f"(d[2]),"+f"(d[3]),"+f"(d[4]),"+f"(d[5]),"+f"(d[6]),"+f"(d[7]),
    "+f"(d[8]),"+f"(d[9]),"+f"(d[10]),"+f"(d[11]),"+f"(d[12]),"+f"(d[13]),"+f"(d[14]),"+f"(d[15])
  : "r"(a0), "r"(a1), "r"(a2), "r"(a3), "l"(db), "r"(sc), "n"(TB));
}
template<int TB> __device__ __forceinline__ void wgmma_rs_n40(float (&d)[20], uint32_t a0, uint32_t a1, uint32_t a2, uint32_t a3, uint64_t db, int sc){
  asm volatile("{\n.reg .pred p;\nsetp.ne.b32 p, %25, 0;\n"
  "wgmma.mma_async.sync.aligned.m64n40k16.f32.bf16.bf16 {%0,%1,%2,%3,%4,%5,%6,%7,%8,%9,%10,%11,%12,%13,%14,%15,%16,%17,%18,%19}, {%20,%21,%22,%23}, %24, p, 1, 1, %26;\n}\n"
  : "+f"(d[0]),"+f"(d[1]),"+f"(d[2]),"+f"(d[3]),"+f"(d[4]),"+f"(d[5]),"+f"(d[6]),"+f"(d[7]),
    "+f"(d[8]),"+f"(d[9]),"+f"(d[10]),"+f"(d[11]),"+f"(d[12]),"+f"(d[13]),"+f"(d[14]),"+f"(d[15]),
    "+f"(d[16]),"+f"(d[17]),"+f"(d[18]),"+f"(d[19])
  : "r"(a0), "r"(a1), "r"(a2), "r"(a3), "l"(db), "r"(sc), "n"(TB));
}
template<int TB> __device__ __forceinline__ void wgmma_rs_n40_z(float (&d)[20], uint32_t a0, uint32_t a1, uint32_t a2, uint32_t a3, uint64_t db){
  asm volatile("wgmma.mma_async.sync.aligned.m64n40k16.f32.bf16.bf16 {%0,%1,%2,%3,%4,%5,%6,%7,%8,%9,%10,%11,%12,%13,%14,%15,%16,%17,%18,%19}, {%20,%21,%22,%23}, %24, 0, 1, 1, %25;\n"
  : "=f"(d[0]),"=f"(d[1]),"=f"(d[2]),"=f"(d[3]),"=f"(d[4]),"=f"(d[5]),"=f"(d[6]),"=f"(d[7]),
    "=f"(d[8]),"=f"(d[9]),"=f"(d[10]),"=f"(d[11]),"=f"(d[12]),"=f"(d[13]),"=f"(d[14]),"=f"(d[15]),
    "=f"(d[16]),"=f"(d[17]),"=f"(d[18]),"=f"(d[19])
  : "r"(a0), "r"(a1), "r"(a2), "r"(a3), "l"(db), "n"(TB));
}
template<int TB> __device__ __forceinline__ void wgmma_rs_n64(float (&d)[32], uint32_t a0, uint32_t a1, uint32_t a2, uint32_t a3, uint64_t db, int sc){
  asm volatile("{\n.reg .pred p;\nsetp.ne.b32 p, %37, 0;\n"
  "wgmma.mma_async.sync.aligned.m64n64k16.f32.bf16.bf16 {%0,%1,%2,%3,%4,%5,%6,%7,%8,%9,%10,%11,%12,%13,%14,%15,%16,%17,%18,%19,%20,%21,%22,%23,%24,%25,%26,%27,%28,%29,%30,%31}, {%32,%33,%34,%35}, %36, p, 1, 1, %38;\n}\n"
  : "+f"(d[0]),"+f"(d[1]),"+f"(d[2]),"+f"(d[3]),"+f"(d[4]),"+f"(d[5]),"+f"(d[6]),"+f"(d[7]),
    "+f"(d[8]),"+f"(d[9]),"+f"(d[10]),"+f"(d[11]),"+f"(d[12]),"+f"(d[13]),"+f"(d[14]),"+f"(d[15]),
    "+f"(d[16]),"+f"(d[17]),"+f"(d[18]),"+f"(d[19]),"+f"(d[20]),"+f"(d[21]),"+f"(d[22]),"+f"(d[23]),
    "+f"(d[24]),"+f"(d[25]),"+f"(d[26]),"+f"(d[27]),"+f"(d[28]),"+f"(d[29]),"+f"(d[30]),"+f"(d[31])
  : "r"(a0), "r"(a1), "r"(a2), "r"(a3), "l"(db), "r"(sc), "n"(TB));
}
template<int TB> __device__ __forceinline__ void wgmma_rs_n64_z(float (&d)[32], uint32_t a0, uint32_t a1, uint32_t a2, uint32_t a3, uint64_t db){
  asm volatile("wgmma.mma_async.sync.aligned.m64n64k16.f32.bf16.bf16 {%0,%1,%2,%3,%4,%5,%6,%7,%8,%9,%10,%11,%12,%13,%14,%15,%16,%17,%18,%19,%20,%21,%22,%23,%24,%25,%26,%27,%28,%29,%30,%31}, {%32,%33,%34,%35}, %36, 0, 1, 1, %37;\n"
  : "=f"(d[0]),"=f"(d[1]),"=f"(d[2]),"=f"(d[3]),"=f"(d[4]),"=f"(d[5]),"=f"(d[6]),"=f"(d[7]),
    "=f"(d[8]),"=f"(d[9]),"=f"(d[10]),"=f"(d[11]),"=f"(d[12]),"=f"(d[13]),"=f"(d[14]),"=f"(d[15]),
    "=f"(d[16]),"=f"(d[17]),"=f"(d[18]),"=f"(d[19]),"=f"(d[20]),"=f"(d[21]),"=f"(d[22]),"=f"(d[23]),
    "=f"(d[24]),"=f"(d[25]),"=f"(d[26]),"=f"(d[27]),"=f"(d[28]),"=f"(d[29]),"=f"(d[30]),"=f"(d[31])
  : "r"(a0), "r"(a1), "r"(a2), "r"(a3), "l"(db), "n"(TB));
}
template<int TB> __device__ __forceinline__ void wgmma_rs_n72(float (&d)[36], uint32_t a0, uint32_t a1, uint32_t a2, uint32_t a3, uint64_t db, int sc){
  asm volatile("{\n.reg .pred p;\nsetp.ne.b32 p, %41, 0;\n"
  "wgmma.mma_async.sync.aligned.m64n72k16.f32.bf16.bf16 {%0,%1,%2,%3,%4,%5,%6,%7,%8,%9,%10,%11,%12,%13,%14,%15,%16,%17,%18,%19,%20,%21,%22,%23,%24,%25,%26,%27,%28,%29,%30,%31,%32,%33,%34,%35}, {%36,%37,%38,%39}, %40, p, 1, 1, %42;\n}\n"
  : "+f"(d[0]),"+f"(d[1]),"+f"(d[2]),"+f"(d[3]),"+f"(d[4]),"+f"(d[5]),"+f"(d[6]),"+f"(d[7]),
    "+f"(d[8]),"+f"(d[9]),"+f"(d[10]),"+f"(d[11]),"+f"(d[12]),"+f"(d[13]),"+f"(d[14]),"+f"(d[15]),
    "+f"(d[16]),"+f"(d[17]),"+f"(d[18]),"+f"(d[19]),"+f"(d[20]),"+f"(d[21]),"+f"(d[22]),"+f"(d[23]),
    "+f"(d[24]),"+f"(d[25]),"+f"(d[26]),"+f"(d[27]),"+f"(d[28]),"+f"(d[29]),"+f"(d[30]),"+f"(d[31]),
    "+f"(d[32]),"+f"(d[33]),"+f"(d[34]),"+f"(d[35])
  : "r"(a0), "r"(a1), "r"(a2), "r"(a3), "l"(db), "r"(sc), "n"(TB));
}
template<int TB> __device__ __forceinline__ void wgmma_rs_n72_z(float (&d)[36], uint32_t a0, uint32_t a1, uint32_t a2, uint32_t a3, uint64_t db){
  asm volatile("wgmma.mma_async.sync.aligned.m64n72k16.f32.bf16.bf16 {%0,%1,%2,%3,%4,%5,%6,%7,%8,%9,%10,%11,%12,%13,%14,%15,%16,%17,%18,%19,%20,%21,%22,%23,%24,%25,%26,%27,%28,%29,%30,%31,%32,%33,%34,%35}, {%36,%37,%38,%39}, %40, 0, 1, 1, %41;\n"
  : "=f"(d[0]),"=f"(d[1]),"=f"(d[2]),"=f"(d[3]),"=f"(d[4]),"=f"(d[5]),"=f"(d[6]),"=f"(d[7]),
    "=f"(d[8]),"=f"(d[9]),"=f"(d[10]),"=f"(d[11]),"=f"(d[12]),"=f"(d[13]),"=f"(d[14]),"=f"(d[15]),
    "=f"(d[16]),"=f"(d[17]),"=f"(d[18]),"=f"(d[19]),"=f"(d[20]),"=f"(d[21]),"=f"(d[22]),"=f"(d[23]),
    "=f"(d[24]),"=f"(d[25]),"=f"(d[26]),"=f"(d[27]),"=f"(d[28]),"=f"(d[29]),"=f"(d[30]),"=f"(d[31]),
    "=f"(d[32]),"=f"(d[33]),"=f"(d[34]),"=f"(d[35])
  : "r"(a0), "r"(a1), "r"(a2), "r"(a3), "l"(db), "n"(TB));
}
template<int TA,int TB> __device__ __forceinline__ void wgmma_ss_n128(float (&d)[64], uint64_t da, uint64_t db, int sc){
  asm volatile("{\n.reg .pred p;\nsetp.ne.b32 p, %66, 0;\n"
  "wgmma.mma_async.sync.aligned.m64n128k16.f32.bf16.bf16 {%0,%1,%2,%3,%4,%5,%6,%7,%8,%9,%10,%11,%12,%13,%14,%15,%16,%17,%18,%19,%20,%21,%22,%23,%24,%25,%26,%27,%28,%29,%30,%31,%32,%33,%34,%35,%36,%37,%38,%39,%40,%41,%42,%43,%44,%45,%46,%47,%48,%49,%50,%51,%52,%53,%54,%55,%56,%57,%58,%59,%60,%61,%62,%63}, %64, %65, p, 1, 1, %67, %68;\n}\n"
  : "+f"(d[0]),"+f"(d[1]),"+f"(d[2]),"+f"(d[3]),"+f"(d[4]),"+f"(d[5]),"+f"(d[6]),"+f"(d[7]),
    "+f"(d[8]),"+f"(d[9]),"+f"(d[10]),"+f"(d[11]),"+f"(d[12]),"+f"(d[13]),"+f"(d[14]),"+f"(d[15]),
    "+f"(d[16]),"+f"(d[17]),"+f"(d[18]),"+f"(d[19]),"+f"(d[20]),"+f"(d[21]),"+f"(d[22]),"+f"(d[23]),
    "+f"(d[24]),"+f"(d[25]),"+f"(d[26]),"+f"(d[27]),"+f"(d[28]),"+f"(d[29]),"+f"(d[30]),"+f"(d[31]),
    "+f"(d[32]),"+f"(d[33]),"+f"(d[34]),"+f"(d[35]),"+f"(d[36]),"+f"(d[37]),"+f"(d[38]),"+f"(d[39]),
    "+f"(d[40]),"+f"(d[41]),"+f"(d[42]),"+f"(d[43]),"+f"(d[44]),"+f"(d[45]),"+f"(d[46]),"+f"(d[47]),
    "+f"(d[48]),"+f"(d[49]),"+f"(d[50]),"+f"(d[51]),"+f"(d[52]),"+f"(d[53]),"+f"(d[54]),"+f"(d[55]),
    "+f"(d[56]),"+f"(d[57]),"+f"(d[58]),"+f"(d[59]),"+f"(d[60]),"+f"(d[61]),"+f"(d[62]),"+f"(d[63])
  : "l"(da), "l"(db), "r"(sc), "n"(TA), "n"(TB));
}
template<int TA,int TB> __device__ __forceinline__ void wgmma_ss_n128_z(float (&d)[64], uint64_t da, uint64_t db){
  asm volatile("wgmma.mma_async.sync.aligned.m64n128k16.f32.bf16.bf16 {%0,%1,%2,%3,%4,%5,%6,%7,%8,%9,%10,%11,%12,%13,%14,%15,%16,%17,%18,%19,%20,%21,%22,%23,%24,%25,%26,%27,%28,%29,%30,%31,%32,%33,%34,%35,%36,%37,%38,%39,%40,%41,%42,%43,%44,%45,%46,%47,%48,%49,%50,%51,%52,%53,%54,%55,%56,%57,%58,%59,%60,%61,%62,%63}, %64, %65, 0, 1, 1, %66, %67;\n"
  : "=f"(d[0]),"=f"(d[1]),"=f"(d[2]),"=f"(d[3]),"=f"(d[4]),"=f"(d[5]),"=f"(d[6]),"=f"(d[7]),
    "=f"(d[8]),"=f"(d[9]),"=f"(d[10]),"=f"(d[11]),"=f"(d[12]),"=f"(d[13]),"=f"(d[14]),"=f"(d[15]),
    "=f"(d[16]),"=f"(d[17]),"=f"(d[18]),"=f"(d[19]),"=f"(d[20]),"=f"(d[21]),"=f"(d[22]),"=f"(d[23]),
    "=f"(d[24]),"=f"(d[25]),"=f"(d[26]),"=f"(d[27]),"=f"(d[28]),"=f"(d[29]),"=f"(d[30]),"=f"(d[31]),
    "=f"(d[32]),"=f"(d[33]),"=f"(d[34]),"=f"(d[35]),"=f"(d[36]),"=f"(d[37]),"=f"(d[38]),"=f"(d[39]),
    "=f"(d[40]),"=f"(d[41]),"=f"(d[42]),"=f"(d[43]),"=f"(d[44]),"=f"(d[45]),"=f"(d[46]),"=f"(d[47]),
    "=f"(d[48]),"=f"(d[49]),"=f"(d[50]),"=f"(d[51]),"=f"(d[52]),"=f"(d[53]),"=f"(d[54]),"=f"(d[55]),
    "=f"(d[56]),"=f"(d[57]),"=f"(d[58]),"=f"(d[59]),"=f"(d[60]),"=f"(d[61]),"=f"(d[62]),"=f"(d[63])
  : "l"(da), "l"(db), "n"(TA), "n"(TB));
}
template<int TA,int TB> __device__ __forceinline__ void wgmma_ss_n16(float (&d)[8], uint64_t da, uint64_t db, int sc){
  asm volatile("{\n.reg .pred p;\nsetp.ne.b32 p, %10, 0;\n"
  "wgmma.mma_async.sync.aligned.m64n16k16.f32.bf16.bf16 {%0,%1,%2,%3,%4,%5,%6,%7}, %8, %9, p, 1, 1, %11, %12;\n}\n"
  : "+f"(d[0]),"+f"(d[1]),"+f"(d[2]),"+f"(d[3]),"+f"(d[4]),"+f"(d[5]),"+f"(d[6]),"+f"(d[7])
  : "l"(da), "l"(db), "r"(sc), "n"(TA), "n"(TB));
}
template<int TA,int TB> __device__ __forceinline__ void wgmma_ss_n64(float (&d)[32], uint64_t da, uint64_t db, int sc){
  asm volatile("{\n.reg .pred p;\nsetp.ne.b32 p, %34, 0;\n"
  "wgmma.mma_async.sync.aligned.m64n64k16.f32.bf16.bf16 {%0,%1,%2,%3,%4,%5,%6,%7,%8,%9,%10,%11,%12,%13,%14,%15,%16,%17,%18,%19,%20,%21,%22,%23,%24,%25,%26,%27,%28,%29,%30,%31}, %32, %33, p, 1, 1, %35, %36;\n}\n"
  : "+f"(d[0]),"+f"(d[1]),"+f"(d[2]),"+f"(d[3]),"+f"(d[4]),"+f"(d[5]),"+f"(d[6]),"+f"(d[7]),
    "+f"(d[8]),"+f"(d[9]),"+f"(d[10]),"+f"(d[11]),"+f"(d[12]),"+f"(d[13]),"+f"(d[14]),"+f"(d[15]),
    "+f"(d[16]),"+f"(d[17]),"+f"(d[18]),"+f"(d[19]),"+f"(d[20]),"+f"(d[21]),"+f"(d[22]),"+f"(d[23]),
    "+f"(d[24]),"+f"(d[25]),"+f"(d[26]),"+f"(d[27]),"+f"(d[28]),"+f"(d[29]),"+f"(d[30]),"+f"(d[31])
  : "l"(da), "l"(db), "r"(sc), "n"(TA), "n"(TB));
}

constexpr uint32_t SB     = 1024;
constexpr uint32_t SM_R   = SB;
constexpr uint32_t SM_KV  = SB + 131072;
constexpr uint32_t SM_Q   = SB + 196608;
constexpr uint32_t SM_BAR = SB + 229376;
constexpr uint32_t SMEM_BYTES = 229376 + 1024;
__device__ __forceinline__ uint32_t head_wq(uint32_t st) { return SB + ((0x01BA9C0Cu >> (4 * st)) & 15) * 16384; }
constexpr uint32_t B_HX = SM_BAR, B_HK = SM_BAR + 64, B_HW = SM_BAR + 72;
constexpr uint32_t B_FULL = SM_BAR + 136, B_EMPTY = SM_BAR + 168, B_KVFULL = SM_BAR + 200, B_FX = SM_BAR + 232;
constexpr uint32_t B_HD0 = SM_BAR + 248, B_KINFO = SM_BAR + 256, B_KVSENT = SM_BAR + 264, B_QFREE = SM_BAR + 272;
constexpr uint32_t B_HT = SM_BAR + 312, B_HD1 = B_HT - 24;
constexpr uint32_t B_KVEMPTY = SM_BAR + 320;
constexpr uint32_t B_END = SM_BAR + 352;
constexpr uint32_t B_QRDY = SM_BAR + 360, B_GPART = SM_BAR + 368, B_OSTORE = SM_BAR + 376, B_OLAST = SM_BAR + 392, B_GSTORE = SM_BAR + 408;
constexpr uint32_t SM_WMAX = SM_BAR + 448, SM_KINFO = SM_BAR + 480, SM_UNSAFE = SM_BAR + 484, SM_DUMMY = SM_BAR + 496;

constexpr int F_KVB = 0;
constexpr int F_COL = 128, F_ROW = F_COL + 8 * 32, F_DONE = F_ROW + 16 * 32;
__device__ __forceinline__ int c_part(int j, int t) { return F_COL + j * 32 + t; }
__device__ __forceinline__ int c_red(int j) { return F_COL + j * 32 + 2; }
__device__ __forceinline__ int c_row(int i, int p) { return F_ROW + i * 32 + p; }
struct Small {
  uint32_t flags[1024];
  __nv_bfloat16 kvb[2048 * 64];
  uint32_t blob[8 * 4096];
  float zpart[16 * 16 * 64];
  float4 part[16 * 16 * 512];
};
__device__ __align__(1024) Small g_s;
__device__ __align__(1024) __nv_bfloat16 g_oa[2048 * 1024];
__device__ __align__(1024) __nv_bfloat16 g_ob[2048 * 1024];
#define TLREC(k)

struct Maps {
  CUtensorMap xBh, wqh, wkv[2], kvS, kvb;
  CUtensorMap x[2], w[3];
  CUtensorMap oL[2], wo[2], st[2];
  CUtensorMap obH, obS;
};

__device__ __forceinline__ void wg_fence() { asm volatile("wgmma.fence.sync.aligned;" ::: "memory"); }
__device__ __forceinline__ void wg_commit() { asm volatile("wgmma.commit_group.sync.aligned;" ::: "memory"); }
template <int N> __device__ __forceinline__ void wg_wait() { asm volatile("wgmma.wait_group.sync.aligned %0;" ::"n"(N) : "memory"); }
template <int N> __device__ __forceinline__ void pin(float (&d)[N]) {
#pragma unroll
  for (int i = 0; i < N; i++) asm volatile("" : "+f"(d[i])::"memory");
}
template <int N> __device__ __forceinline__ void pin(uint32_t (&d)[N]) {
#pragma unroll
  for (int i = 0; i < N; i++) asm volatile("" : "+r"(d[i])::"memory");
}
template <int N> __device__ __forceinline__ void fresh(float (&d)[N]) {
#pragma unroll
  for (int i = 0; i < N; i++) asm volatile("" : "=f"(d[i]));
}
__device__ __forceinline__ uint64_t mkdesc(uint32_t a16, uint32_t lbo, uint32_t sbo, uint32_t sw) {
  uint32_t lo = a16 + ((lbo >> 4) << 16), hi = (sbo >> 4) | (sw << 30);
  uint64_t d;
  asm("mov.b64 %0,{%1,%2};" : "=l"(d) : "r"(lo), "r"(hi));
  return d;
}
__device__ __forceinline__ uint64_t desc(uint32_t a16) { return mkdesc(a16, 8192, 1024, 1); }

__device__ __forceinline__ float ex2(float x) { float y; asm("ex2.approx.ftz.f32 %0,%1;" : "=f"(y) : "f"(x)); return y; }
__device__ __forceinline__ float rcp(float x) { float y; asm("rcp.approx.ftz.f32 %0,%1;" : "=f"(y) : "f"(x)); return y; }
__device__ __forceinline__ uint32_t pack(float lo, float hi) { uint32_t r; asm("cvt.rn.bf16x2.f32 %0,%1,%2;" : "=r"(r) : "f"(hi), "f"(lo)); return r; }
__device__ __forceinline__ uint32_t phi2(float t0, float t1) {
  const float e0 = __saturatef(ex2(t0 * 1.4426950408889634f) + 1e-6f), e1 = __saturatef(ex2(t1 * 1.4426950408889634f) + 1e-6f);
  uint32_t r;
  asm("cvt.rn.relu.bf16x2.f32 %0,%1,%2;" : "=r"(r) : "f"(t1), "f"(t0));
  asm("add.rn.bf16x2 %0,%0,%1;" : "+r"(r) : "r"(pack(e0, e1)));
  return r;
}
__device__ __forceinline__ uint32_t phi2p(uint32_t t) {
  const float e0 = __saturatef(ex2(__uint_as_float(t << 16) * 1.4426950408889634f) + 1e-6f);
  const float e1 = __saturatef(ex2(__uint_as_float(t & 0xffff0000u) * 1.4426950408889634f) + 1e-6f);
  asm("max.NaN.bf16x2 %0,%0,%1;" : "+r"(t) : "r"(0));
  asm("add.rn.bf16x2 %0,%0,%1;" : "+r"(t) : "r"(pack(e0, e1)));
  return t;
}

__device__ __forceinline__ void mbar_init(uint32_t b, uint32_t n) { asm volatile("mbarrier.init.shared::cta.b64 [%0],%1;" ::"r"(b), "r"(n) : "memory"); }
__device__ __forceinline__ void mbar_arrive(uint32_t b) { asm volatile("mbarrier.arrive.shared::cta.b64 _,[%0];" ::"r"(b) : "memory"); }
__device__ __forceinline__ void mbar_arrive_if(uint32_t b, bool p) {
  asm volatile("{\n.reg .pred p;\nsetp.ne.u32 p,%1,0;\n@p mbarrier.arrive.shared::cta.b64 _,[%0];\n}" ::"r"(b), "r"((uint32_t)p) : "memory");
}
__device__ __forceinline__ uint32_t mbar_test(uint32_t b, uint32_t parity) {
  uint32_t ok;
  asm volatile("{\n.reg .pred p;\nmbarrier.test_wait.parity.shared::cta.b64 p,[%1],%2;\nselp.u32 %0,1,0,p;\n}" : "=r"(ok) : "r"(b), "r"(parity) : "memory");
  return ok;
}
__device__ __forceinline__ void mbar_expect(uint32_t b, uint32_t bytes) {
  asm volatile("mbarrier.arrive.expect_tx.shared::cta.b64 _,[%0],%1;" ::"r"(b), "r"(bytes) : "memory");
}
__device__ __forceinline__ void mbar_wait_wd(uint32_t b, uint32_t parity) {
  asm volatile(
      "{\n.reg .pred p;\n.reg .u32 t0;\n"
      "mov.u32 t0,0;\n"
      "MW_LOOP:\n"
      "mbarrier.try_wait.parity.shared::cta.b64 p,[%0],%1,100000;\n"
      "@p bra MW_DONE;\n"
      "add.u32 t0,t0,1;\n"
      "setp.lt.u32 p,t0,20000;\n"
      "@p bra MW_LOOP;\n"
      "trap;\n"
      "MW_DONE:\n}" ::"r"(b), "r"(parity) : "memory");
}
__device__ __forceinline__ void mbar_wait(uint32_t b, uint32_t parity) {
  asm volatile("{\n.reg .pred p;\nMS_LOOP:\nmbarrier.try_wait.parity.shared::cta.b64 p,[%0],%1;\n@!p bra MS_LOOP;\n}" ::"r"(b), "r"(parity) : "memory");
}
__device__ __forceinline__ bool elect_one() {
  uint32_t p;
  asm volatile("{\n.reg .pred p;\nelect.sync _|p,0xffffffff;\nselp.u32 %0,1,0,p;\n}" : "=r"(p));
  return p != 0;
}
template <int ID, int N> __device__ __forceinline__ void bar_sync() { asm volatile("bar.sync %0,%1;" ::"n"(ID), "n"(N) : "memory"); }
__device__ __forceinline__ void fence_async_smem() { asm volatile("fence.proxy.async.shared::cta;" ::: "memory"); }
__device__ __forceinline__ void fence_async_gmem() { asm volatile("fence.proxy.async.global;" ::: "memory"); }
__device__ __forceinline__ void fence_acquire() { asm volatile("fence.acquire.gpu;" ::: "memory"); }

__device__ __forceinline__ void tma2d(uint32_t dst, const CUtensorMap* m, int c0, int c1, uint32_t bar) {
  asm volatile("cp.async.bulk.tensor.2d.shared::cluster.global.mbarrier::complete_tx::bytes [%0],[%1,{%3,%4}],[%2];"
               ::"r"(dst), "l"(m), "r"(bar), "r"(c0), "r"(c1) : "memory");
}
__device__ __forceinline__ void tma3d(uint32_t dst, const CUtensorMap* m, int c0, int c1, int c2, uint32_t bar) {
  asm volatile("cp.async.bulk.tensor.3d.shared::cluster.global.mbarrier::complete_tx::bytes [%0],[%1,{%3,%4,%5}],[%2];"
               ::"r"(dst), "l"(m), "r"(bar), "r"(c0), "r"(c1), "r"(c2) : "memory");
}
__device__ __forceinline__ void tma5d(uint32_t dst, const CUtensorMap* m, int c2, int c3, int c4, uint32_t bar) {
  asm volatile("cp.async.bulk.tensor.5d.shared::cluster.global.mbarrier::complete_tx::bytes [%0],[%1,{%6,%6,%3,%4,%5}],[%2];"
               ::"r"(dst), "l"(m), "r"(bar), "r"(c2), "r"(c3), "r"(c4), "r"(0) : "memory");
}
__device__ __forceinline__ void tma_store2d(const CUtensorMap* m, int c0, int c1, uint32_t src) {
  asm volatile("cp.async.bulk.tensor.2d.global.shared::cta.bulk_group [%0,{%2,%3}],[%1];" ::"l"(m), "r"(src), "r"(c0), "r"(c1) : "memory");
}
__device__ __forceinline__ void bulk_load(uint32_t dst, const void* src, uint32_t bytes, uint32_t bar) {
  asm volatile("cp.async.bulk.shared::cluster.global.mbarrier::complete_tx::bytes [%0],[%1],%2,[%3];" ::"r"(dst), "l"(src), "r"(bytes), "r"(bar) : "memory");
}
__device__ __forceinline__ void bulk_commit() { asm volatile("cp.async.bulk.commit_group;" ::: "memory"); }
__device__ __forceinline__ void bulk_wait() { asm volatile("cp.async.bulk.wait_group 0;" ::: "memory"); }
__device__ __forceinline__ void prefetch_map(const CUtensorMap* m) { asm volatile("prefetch.tensormap [%0];" ::"l"(m) : "memory"); }
__device__ __forceinline__ void stsm4(uint32_t a, uint32_t r0, uint32_t r1, uint32_t r2, uint32_t r3) {
  asm volatile("stmatrix.sync.aligned.m8n8.x4.shared.b16 [%0],{%1,%2,%3,%4};" ::"r"(a), "r"(r0), "r"(r1), "r"(r2), "r"(r3) : "memory");
}
__device__ __forceinline__ void stsm8f(uint32_t a, const float* v) { stsm4(a, pack(v[0], v[1]), pack(v[2], v[3]), pack(v[4], v[5]), pack(v[6], v[7])); }
__device__ __forceinline__ void stsm8s(uint32_t a, const float* v, float s0, float s1) {
  stsm4(a, pack(v[0] * s0, v[1] * s0), pack(v[2] * s1, v[3] * s1), pack(v[4] * s0, v[5] * s0), pack(v[6] * s1, v[7] * s1));
}
__device__ __forceinline__ void load_q(uint32_t (&q)[8], uint32_t a) {
  asm volatile("ldmatrix.sync.aligned.m8n8.x4.shared.b16 {%0,%1,%2,%3},[%4];" : "=r"(q[0]), "=r"(q[1]), "=r"(q[2]), "=r"(q[3]) : "r"(a) : "memory");
  asm volatile("ldmatrix.sync.aligned.m8n8.x4.shared.b16 {%0,%1,%2,%3},[%4];" : "=r"(q[4]), "=r"(q[5]), "=r"(q[6]), "=r"(q[7]) : "r"(a ^ 32) : "memory");
}
__device__ __forceinline__ void sts32(uint32_t a, uint32_t v) { asm volatile("st.shared.u32 [%0],%1;" ::"r"(a), "r"(v) : "memory"); }
__device__ __forceinline__ uint32_t lds32(uint32_t a) { uint32_t v; asm volatile("ld.shared.u32 %0,[%1];" : "=r"(v) : "r"(a) : "memory"); return v; }
__device__ __forceinline__ uint32_t lds_max4(uint32_t a) {
  uint4 v;
  asm volatile("ld.shared.v4.u32 {%0,%1,%2,%3},[%4];" : "=r"(v.x), "=r"(v.y), "=r"(v.z), "=r"(v.w) : "r"(a) : "memory");
  return max(max(v.x, v.y), max(v.z, v.w));
}
__device__ __forceinline__ float quad_sum(float v) { v += __shfl_xor_sync(~0u, v, 1); return v + __shfl_xor_sync(~0u, v, 2); }
__device__ __forceinline__ void cnt_add(uint32_t* c) { asm volatile("red.release.gpu.global.add.u32 [%0],1;" ::"l"(c) : "memory"); }
__device__ __forceinline__ uint32_t cnt_ld(uint32_t* c) {
  uint32_t v;
  asm volatile("ld.acquire.gpu.global.u32 %0,[%1];" : "=r"(v) : "l"(c) : "memory");
  return v;
}
__device__ __forceinline__ void cnt_wait(uint32_t* c, uint32_t target) {
  asm volatile(
      "{\n.reg .pred p;\n.reg .u32 n,v;\n"
      "mov.u32 n,0;\n"
      "CW_LOOP:\n"
      "ld.acquire.gpu.global.u32 v,[%0];\n"
      "setp.ge.u32 p,v,%1;\n"
      "@p bra CW_DONE;\n"
      "nanosleep.u32 40;\n"
      "add.u32 n,n,1;\n"
      "setp.lt.u32 p,n,4000000;\n"
      "@p bra CW_LOOP;\n"
      "trap;\n"
      "CW_DONE:\n}" ::"l"(c), "r"(target) : "memory");
}
__device__ __forceinline__ void sched_pin(float l0, float l1, uint32_t never) {
  asm volatile("{\n.reg .pred p;\nsetp.ne.u32 p,%3,0;\n@p st.shared.v2.f32 [%2],{%0,%1};\n}" ::"f"(l0), "f"(l1), "r"(SM_DUMMY), "r"(never) : "memory");
}

template <bool TR>
__device__ __forceinline__ void gemm_tile(float (&a0)[64], float (&a1)[64], uint32_t n0, uint32_t steps, bool leader) {
  mbar_wait(B_FULL + (n0 & 3) * 8, (n0 >> 2) & 1);
  {
    const uint32_t x = (SM_R >> 4) + (n0 & 3) * 2048, w = x + 1024;
    wg_fence();
    if (TR) wgmma_ss_n128_z<1, 0>(a0, desc(w), desc(x)); else wgmma_ss_n128_z<0, 1>(a0, desc(x), desc(w));
    if (TR) wgmma_ss_n128_z<1, 0>(a1, desc(w + 512), desc(x)); else wgmma_ss_n128_z<0, 1>(a1, desc(x + 512), desc(w));
    wg_commit();
  }
#pragma unroll 1
  for (uint32_t n = n0; n < n0 + steps; n++) {
    const uint32_t x = (SM_R >> 4) + (n & 3) * 2048, w = x + 1024, nn = min(n + 1, n0 + steps - 1);
#pragma unroll
    for (int kk = 0; kk < 4; kk++) {
      if (kk == 0 && n == n0) continue;
      if (kk < 2) wg_fence();
      if (TR) wgmma_ss_n128<1, 0>(a0, desc(w + kk * 128), desc(x + kk * 2), 1);
      else wgmma_ss_n128<0, 1>(a0, desc(x + kk * 2), desc(w + kk * 128), 1);
      if (!(PACE & (TR ? 1 : 2))) { wg_commit(); wg_wait<1>(); }
      if (kk == 0) mbar_arrive_if(B_EMPTY + ((n - 1) & 3) * 8, leader);
      if (TR) wgmma_ss_n128<1, 0>(a1, desc(w + 512 + kk * 128), desc(x + kk * 2), 1);
      else wgmma_ss_n128<0, 1>(a1, desc(x + 512 + kk * 2), desc(w + kk * 128), 1);
      wg_commit();
      if (kk == 3) mbar_wait(B_FULL + (nn & 3) * 8, (nn >> 2) & 1);
      wg_wait<(PACE & (TR ? 1 : 2)) ? 0 : 1>();
    }
  }
  wg_wait<0>();
  pin(a0); pin(a1);
}
__device__ __forceinline__ void q_block(const float* v, uint32_t qa, uint32_t& m) {
  uint32_t p[8], s0, s1;
#pragma unroll
  for (int e = 0; e < 8; e++) p[e] = pack(v[2 * e], v[2 * e + 1]);
  stsm4(qa, p[0], p[1], p[2], p[3]);
  stsm4(qa ^ 32, p[4], p[5], p[6], p[7]);
  asm("mul.rn.bf16x2 %0,%1,%1;" : "=r"(s0) : "r"(p[0]));
  asm("mul.rn.bf16x2 %0,%1,%1;" : "=r"(s1) : "r"(p[1]));
#pragma unroll
  for (int e = 2; e < 8; e += 2) {
    asm("fma.rn.bf16x2 %0,%1,%1,%0;" : "+r"(s0) : "r"(p[e]));
    asm("fma.rn.bf16x2 %0,%1,%1,%0;" : "+r"(s1) : "r"(p[e + 1]));
  }
  asm("max.NaN.bf16x2 %0,%0,%1;" : "+r"(m) : "r"(s0));
  asm("max.NaN.bf16x2 %0,%0,%1;" : "+r"(m) : "r"(s1));
}
__device__ __forceinline__ float q_bound(uint32_t m) { return quad_sum(__uint_as_float(m << 16) + __uint_as_float(m & 0xffff0000u)); }
__device__ __forceinline__ bool bound_exceeded(float qn2) { return !(qn2 * __uint_as_float(lds32(SM_KINFO)) <= 3500.f); }

__device__ __forceinline__ void lin_mma(float (&D)[20], uint32_t (&p)[8], uint32_t kv) {
  pin(p);
  wg_fence();
  wgmma_rs_n40_z<1>(D, p[0], p[1], p[2], p[3], desc(kv));
  wgmma_rs_n40<1>(D, p[4], p[5], p[6], p[7], desc(kv + 128), 1);
  wg_commit();
}
__device__ __forceinline__ void lin_out(float (&D)[20], uint32_t dst) {
  pin(D);
  const float i0 = rcp(D[16] + 1e-6f), i1 = rcp(D[18] + 1e-6f);
  stsm8s(dst, D, i0, i1);
  stsm8s(dst ^ 32, D + 8, i0, i1);
}
template <int M>
__device__ __forceinline__ void final_mma(float (&a)[64], uint32_t lo, uint32_t hi) {
  constexpr int funr = FUNR;
#pragma unroll funr
  for (uint32_t h = lo; h < hi; h++) {
    const uint32_t x = (SM_KV >> 4) + (1 - M) * 2048 + (h >> 1) * 512 + (h & 1) * 4, w = (SM_R >> 4) + 2048 + (h >> 1) * 1024 + (h & 1) * 256;
    wg_fence();
    wgmma_ss_n128<0, 1>(a, desc(x), desc(w), 1);
    wgmma_ss_n128<0, 1>(a, desc(x + 2), desc(w + 128), 1);
  }
  wg_commit();
}
template <int M, int C0, int C1>
__device__ __forceinline__ void final_out(float (&a)[64], uint32_t sts, const CUtensorMap* m, int i, int j, bool issuer) {
  constexpr uint32_t base = SM_R + 3 * 32768 + M * 16384;
#pragma unroll
  for (int g = 4 * C0; g < 4 * C1 + 4; g++) stsm8f(base + (g >> 2) * 8192 + (sts ^ ((g & 3) << 5)), a + 8 * g);
  fence_async_smem();
  bar_sync<1, 128>();
  if (issuer && elect_one()) {
#pragma unroll
    for (int C = C0; C <= C1; C++) tma_store2d(m, 1024 + j * 128 + C * 64, i * 128 + M * 64, base + C * 8192);
    bulk_commit();
  }
}

__device__ __forceinline__ void attn_batch(float (&S)[32], uint32_t (&q)[8], uint32_t k16, float (&O)[16], uint32_t (&P)[16], uint32_t v16, int acc) {
  wg_fence();
#define PV(k, a) wgmma_rs_n32<1>(O, P[4 * k], P[4 * k + 1], P[4 * k + 2], P[4 * k + 3], desc(v16 + 4 + 128 * k), a)
#define QK0 wgmma_rs_n64_z<0>(S, q[0], q[1], q[2], q[3], desc(k16))
#define QK1 wgmma_rs_n64<0>(S, q[4], q[5], q[6], q[7], desc(k16 + 2), 1)
  if (ORD == 0) { QK0; QK1; PV(0, acc); PV(1, 1); PV(2, 1); PV(3, 1); }
  if (ORD == 1) { QK0; PV(0, acc); QK1; PV(1, 1); PV(2, 1); PV(3, 1); }
  if (ORD == 2) { PV(0, acc); QK0; PV(1, 1); QK1; PV(2, 1); PV(3, 1); }
  if (ORD == 3) { PV(0, acc); QK0; PV(1, 1); PV(2, 1); QK1; PV(3, 1); }
  if (ORD == 4) { PV(0, acc); PV(1, 1); QK0; PV(2, 1); QK1; PV(3, 1); }
  if (ORD == 5) { QK0; PV(0, acc); PV(1, 1); QK1; PV(2, 1); PV(3, 1); }
  wg_commit();
}
__device__ __forceinline__ void attn_exp(float (&S)[32], uint32_t (&P)[16], float& l0, float& l1, uint32_t never, float (&Sn)[32], float (&O)[16]) {
#pragma unroll
  for (int i = 0; i < 16; i++) {
    if (i == 16 - PINAT) sched_pin(l0, l1, never);
    const float a = ex2(S[2 * i]), b = ex2(S[2 * i + 1]);
    if (i & 1) { l1 += a; l1 += b; } else { l0 += a; l0 += b; }
    P[i] = pack(a, b);
  }
  pin(P);
  wg_wait<0>();
  pin(Sn); pin(O);
}

__device__ __forceinline__ void attn_finish(float (&O)[16], float l0, float l1, uint32_t oa, uint32_t bar) {
  const float r0 = rcp(quad_sum(l0)), r1 = rcp(quad_sum(l1));
  stsm8s(oa, O, r0, r1);
  stsm8s(oa ^ 32, O + 8, r0, r1);
  fence_async_smem();
  mbar_arrive(bar);
}
__device__ __forceinline__ void mma16816(float* d, const uint32_t* a, uint32_t b0, uint32_t b1) {
  asm("mma.sync.aligned.m16n8k16.row.col.f32.bf16.bf16.f32 {%0,%1,%2,%3},{%4,%5,%6,%7},{%8,%9},{%0,%1,%2,%3};"
      : "+f"(d[0]), "+f"(d[1]), "+f"(d[2]), "+f"(d[3]) : "r"(a[0]), "r"(a[1]), "r"(a[2]), "r"(a[3]), "r"(b0), "r"(b1));
}
__device__ GENERAL_INLINE void attn_general(uint32_t pass, uint32_t qtop, uint32_t a) {
  const uint32_t lane = threadIdx.x & 31;
#pragma unroll 1
  for (; pass < 4; pass++) {
    float m0 = -INFINITY, m1 = -INFINITY, l0 = 0.f, l1 = 0.f, O[16];
    uint32_t q[8];
    if (pass > 0) mbar_wait(B_QRDY, 0);
    load_q(q, qtop - pass * 8192);
#pragma unroll
    for (int e = 0; e < 16; e++) O[e] = 0.f;
#pragma unroll 1
    for (uint32_t b = 0; b < 64; b++) {
      const uint32_t s = (b >> 2) & 3, kb = SM_KV + (b & 15) * 4096;
      mbar_wait(B_KVFULL + s * 8, (b >> 4) & 1);
      float S[16];
      uint32_t P[8];
#pragma unroll
      for (int n = 0; n < 4; n++) {
        uint32_t k[4];
        asm volatile("ldmatrix.sync.aligned.m8n8.x4.shared.b16 {%0,%1,%2,%3},[%4];" : "=r"(k[0]), "=r"(k[1]), "=r"(k[2]), "=r"(k[3])
                     : "r"(kb + n * 1024 + (lane & 7) * 128 + (((lane >> 3) ^ (lane & 7)) << 4)) : "memory");
        S[4 * n] = S[4 * n + 1] = S[4 * n + 2] = S[4 * n + 3] = 0.f;
        mma16816(S + 4 * n, q, k[0], k[1]);
        mma16816(S + 4 * n, q + 4, k[2], k[3]);
      }
      float x0 = m0, x1 = m1;
#pragma unroll
      for (int e = 0; e < 4; e++) {
        x0 = fmaxf(x0, fmaxf(S[4 * e], S[4 * e + 1]));
        x1 = fmaxf(x1, fmaxf(S[4 * e + 2], S[4 * e + 3]));
      }
      x0 = fmaxf(x0, __shfl_xor_sync(~0u, x0, 1)); x1 = fmaxf(x1, __shfl_xor_sync(~0u, x1, 1));
      x0 = fmaxf(x0, __shfl_xor_sync(~0u, x0, 2)); x1 = fmaxf(x1, __shfl_xor_sync(~0u, x1, 2));
      const float y0 = x0 == -INFINITY ? 0.f : x0, y1 = x1 == -INFINITY ? 0.f : x1;
      const float al0 = ex2(m0 - y0), al1 = ex2(m1 - y1);
      m0 = x0; m1 = x1;
      l0 *= al0; l1 *= al1;
#pragma unroll
      for (int e = 0; e < 4; e++) {
        const float pa = ex2(S[4 * e] - y0), pb = ex2(S[4 * e + 1] - y0), pc = ex2(S[4 * e + 2] - y1), pd = ex2(S[4 * e + 3] - y1);
        l0 += pa + pb; l1 += pc + pd;
        P[2 * e] = pack(pa, pb); P[2 * e + 1] = pack(pc, pd);
        O[4 * e] *= al0; O[4 * e + 1] *= al0; O[4 * e + 2] *= al1; O[4 * e + 3] *= al1;
      }
#pragma unroll
      for (int n = 0; n < 4; n++) {
        uint32_t v[4];
        asm volatile("ldmatrix.sync.aligned.m8n8.x4.trans.shared.b16 {%0,%1,%2,%3},[%4];" : "=r"(v[0]), "=r"(v[1]), "=r"(v[2]), "=r"(v[3])
                     : "r"(kb + lane * 128 + (((4 + n) ^ (lane & 7)) << 4)) : "memory");
        mma16816(O + 4 * n, P, v[0], v[1]);
        mma16816(O + 4 * n, P + 4, v[2], v[3]);
      }
      if ((b & 3) == 3) {
        asm volatile("bar.sync %0,128;" ::"r"(4 + a) : "memory");
        mbar_arrive_if(B_KVEMPTY + s * 8, (threadIdx.x & 127) == 0);
      }
    }
    attn_finish(O, l0, l1, qtop - pass * 8192, (pass == 3 ? B_OLAST : B_OSTORE) + a * 8);
  }
}

__device__ __noinline__ void kv_reduce(Small* gs, int hp, int i) {
  const int lane = threadIdx.x & 31;
  const float* zp = gs->zpart + (hp * 16 + (lane >> 2)) * 64 + 4 * i + (lane & 3);
  float z = __ldcg(zp) + __ldcg(zp + 8 * 64);
  const float4* pp = gs->part + hp * 16 * 512 + i * 32 + lane;
  float4 acc = make_float4(0.f, 0.f, 0.f, 0.f);
#pragma unroll 1
  for (int r = 0; r < 16; r += 4) {
    const float4 v0 = __ldcg(pp + (r + 0) * 512), v1 = __ldcg(pp + (r + 1) * 512), v2 = __ldcg(pp + (r + 2) * 512), v3 = __ldcg(pp + (r + 3) * 512);
    acc.x += (v0.x + v1.x) + (v2.x + v3.x); acc.y += (v0.y + v1.y) + (v2.y + v3.y);
    acc.z += (v0.z + v1.z) + (v2.z + v3.z); acc.w += (v0.w + v1.w) + (v2.w + v3.w);
  }
  z += __shfl_xor_sync(~0u, z, 4); z += __shfl_xor_sync(~0u, z, 8); z += __shfl_xor_sync(~0u, z, 16);
  uint32_t* blob = gs->blob + hp * 2048;
  const int q = i >> 2, d0 = (i & 3) * 16 + (lane >> 2);
  uint32_t* bp = blob + d0 * 32 + ((q ^ (d0 & 7)) << 2) + (lane & 3);
  bp[0] = pack(acc.x, acc.y);
  bp[8 * 32] = pack(acc.z, acc.w);
  const int d = 4 * i + (lane & 3);
  if (lane < 16) blob[d * 32 + ((4 ^ (d & 7)) << 2) + (lane >> 2)] = pack(z, z);
  fence_async_gmem();
  __syncwarp();
  if (lane == 0) cnt_add(gs->flags + c_red(hp >> 1));
}

__global__ void __launch_bounds__(512, 1) fused_kernel(int never, Small* __restrict__ gs, const __grid_constant__ Maps mp) {
  extern __shared__ __align__(1024) char smem_raw[];
  const int warp = __shfl_sync(~0u, (int)(((ROLEMAP >> ((threadIdx.x >> 7) * 4)) & 3) * 4 + ((threadIdx.x >> 5) & 3)), 0);
  const int lane = threadIdx.x & 31;
  const int j = (blockIdx.x & 3) + ((blockIdx.x >> 6) << 2), i = (blockIdx.x >> 2) & 15;
  const uint32_t hf = j >> 2;

  if (warp == 0) {
    if (elect_one()) {
#pragma unroll
      for (int s = 0; s < 10; s++) mbar_init(SM_BAR + s * 8, 1);
      asm volatile("fence.mbarrier_init.release.cluster;" ::: "memory");
      fence_async_smem();
    }
    TLREC(60);
#pragma unroll 1
    for (uint32_t st = 0; st < 8; st++)
      if (elect_one()) {
        mbar_expect(B_HX + st * 8, 16384);
        tma3d(SB + st * 16384, &mp.xBh, 0, i * 128 + hf * 64, st * 2, B_HX + st * 8);
        if (st == WPOS) {
          mbar_expect(B_HK, 65536);
          tma2d(SM_KV, &mp.wkv[(j >> 1) & 1], 0, 0, B_HK);
          tma2d(SM_KV + 32768, &mp.wkv[(j >> 1) & 1], 0, 256, B_HK);
        }
        if (st == QPOS) {
          mbar_expect(B_HW, 16384);
          tma2d(SM_Q, &mp.wqh, j * 128, 0, B_HW);
        }
        if (WQPF && st == 7 && i >= WQPF && i < 8)
          asm volatile("cp.async.bulk.prefetch.tensor.2d.L2.global [%0,{%1,%2}];" ::"l"(&mp.wqh), "r"(j * 128), "r"(i * 128) : "memory");
      }
  } else if (warp < 3) {
    if (elect_one()) {
      if (warp == 1) {
#pragma unroll 1
        for (int s = 10; s < 39; s++) mbar_init(SM_BAR + s * 8, 1);
      } else {
#pragma unroll 1
        for (int s = 39; s < 55; s++) mbar_init(SM_BAR + s * 8, s < 44 ? 2 : s == 44 ? 15 : 128);
        sts32(SM_UNSAFE, 0);
      }
      asm volatile("fence.mbarrier_init.release.cluster;" ::: "memory");
      fence_async_smem();
    }
  }
  __syncthreads();

  if (warp < 4) {
    asm volatile("setmaxnreg.dec.sync.aligned.u32 %0;" ::"n"(REG_S));
    if (warp == 0) {
#pragma unroll 1
      for (int w = 1; w < 8; w++) {
        mbar_wait(B_HT - min(max(w - 2, 0), 4) * 8, 0);
        if (elect_one()) {
          mbar_expect(B_HW + w * 8, 16384);
          tma2d(head_wq(w), &mp.wqh, j * 128, w * 128, B_HW + w * 8);
        }
      }
      mbar_wait(B_HD0, 0);
      mbar_wait(B_KINFO, 0);
#pragma unroll 1
      for (uint32_t n = 0; n < 64; n++) {
        const uint32_t t = n >> 4, s = n & 3, f = B_FULL + s * 8, k = (n & 15) * 64;
        const bool kvt = t == 1 || t == 2;
        mbar_wait(B_EMPTY + s * 8, ((n >> 2) & 1) ^ 1);
        if (elect_one()) {
          mbar_expect(f, 32768);
          tma2d(SM_R + s * 32768, &mp.x[t > 0], k, i * 128, f);
          tma3d(SM_R + s * 32768 + 16384, &mp.w[(t + 1) >> 1], kvt ? (2 * j + t - 1) * 64 : 0, k, kvt ? 1 : 2 * j, f);
        }
      }
      mbar_wait(B_EMPTY, 1);
      cnt_wait(gs->flags + c_red(j), 32);
      fence_async_gmem();
      if (elect_one()) {
        mbar_expect(B_FULL, 16384);
        bulk_load(SM_R, gs->blob + j * 4096, 16384, B_FULL);
      }
      uint32_t nx = 0, ready = 0;
#pragma unroll 1
      for (uint32_t m = 0; m < 30; m++) {
        const uint32_t s = (m + 1) & 3, f = B_FULL + s * 8, kb = m < 16 ? (m & 7) * 2 + (m >> 3) : m - 16;
        mbar_wait(B_EMPTY + s * 8, (((m + 1) >> 2) & 1) ^ 1);
        if (elect_one()) {
          mbar_expect(f, 32768);
          tma5d(SM_R + s * 32768 + 16384, &mp.wo[m >> 4], kb >> 2, m < 28 ? (kb & 3) * 2 : (m & 3) * 4 + 2, 2 * j, f);
          if (m >= 28) tma5d(SM_R + s * 32768, &mp.wo[1], 3, (m & 3) * 4, 2 * j, f);
        }
        if (ready <= m) {
          if (m & 1) cnt_wait(gs->flags + c_row(i, m >> 3), 8);
          if (__shfl_sync(~0u, cnt_ld(gs->flags + c_row(i, m >> 3)), 0) >= 8) ready += 8;
          fence_async_gmem();
        }
#pragma unroll 1
        for (; nx <= m && nx < ready && nx < 28; nx++)
          if (elect_one())
            tma2d(SM_R + ((nx + 1) & 3) * 32768, &mp.oL[nx >> 4], (nx < 16 ? (nx & 7) * 2 + (nx >> 3) : nx - 16) * 64, i * 128, B_FULL + ((nx + 1) & 3) * 8);
      }
      mbar_wait(B_FX, 0);
      mbar_wait(B_FX + 8, 0);
      uint32_t last = 0;
      if (elect_one()) asm volatile("atom.relaxed.gpu.global.add.u32 %0,[%1],1;" : "=r"(last) : "l"(gs->flags + F_DONE) : "memory");
      if (__reduce_max_sync(~0u, last) == gridDim.x - 1) {
        fence_acquire();
        uint4* fl = (uint4*)gs->flags;
        fl[lane] = make_uint4(0, 0, 0, 0);
        if (lane < 25) { fl[32 + lane * 8] = make_uint4(0, 0, 0, 0); fl[33 + lane * 8] = make_uint4(0, 0, 0, 0); }
      }
    } else if (warp == 3) {
      if ((uint32_t)__cvta_generic_to_shared(smem_raw) != SB) __trap();
      #pragma unroll 1
      for (int k = 0; k < 15; k++) if (elect_one()) prefetch_map(&mp.kvS + k);
#pragma unroll 1
      for (int t = 0; t < 2; t++) {
        mbar_wait(B_GPART, t);
        if (elect_one()) cnt_add(gs->flags + c_part(j, t));
        __syncwarp();
        cnt_wait(gs->flags + c_part(j, t), 16);
        kv_reduce(gs, 2 * j + t, i);
        TLREC(18 + t);
      }
#pragma unroll 1
      for (int r = 0; r < 8; r++) {
        if (r <= 4) mbar_wait(B_GSTORE + (r & 3) * 8, r >> 2); else __nanosleep(STNS);
        if (elect_one()) {
          tma_store2d(&mp.st[r >> 2], j * 128 + (r & 2) * 32, i * 128 + (r & 1) * 64, r < 4 ? SM_R + 3 * 32768 + r * 8192 : r == 4 ? SM_R : SM_Q + (r - 4) * 8192);
          bulk_commit();
          bulk_wait();
          if (r == 3 || r == 4) mbar_arrive(B_EMPTY + (r & 3) * 8);
          if ((r & 5) == 1) cnt_add(gs->flags + c_row(i, r >> 1));
        }
        TLREC(36 + (r >> 2));
      }
    } else {
      if (warp == 1) {
        uint4 a;
        uint32_t spins = 0, g = 0;
        mbar_wait(B_HD1, 0);
        while (true) {
          asm volatile("ld.acquire.gpu.global.v4.u32 {%0,%1,%2,%3},[%4];" : "=r"(a.x), "=r"(a.y), "=r"(a.z), "=r"(a.w) : "l"(gs->flags + F_KVB + lane * 4) : "memory");
          const uint32_t rdy = __ballot_sync(~0u, (a.x & a.y & a.z & a.w & 1u) != 0);
          fence_async_gmem();
          if (g == 0 && (rdy & 3u) == 3u) {
            g = 1;
            if (elect_one()) {
              mbar_expect(B_KVFULL, 16384);
              tma2d(SM_KV, &mp.kvb, 0, 0, B_KVFULL);
            }
          }
          if (rdy == ~0u) break;
          __nanosleep(POLLNS);
          if (++spins > 4000000u) __trap();
        }
        const uint32_t knm = __reduce_max_sync(~0u, __float_as_uint(__uint_as_float(a.x) + __uint_as_float(a.y)));
        const uint32_t vnm = __reduce_max_sync(~0u, max(a.z, a.w));
        if (elect_one()) {
          sts32(SM_KINFO, vnm - 0x17800000u <= 0x50000000u ? knm : 0x7f800000u);
          mbar_arrive(B_KINFO);
        }
        TLREC(8);
        mbar_wait(B_HD0, 0);
#pragma unroll 1
        for (g = 1; g < 64; g++) {
          const uint32_t s = g & 3;
          mbar_wait(B_KVEMPTY + s * 8, ((g >> 2) & 1) ^ 1);
          if (elect_one()) {
            mbar_expect(B_KVFULL + s * 8, 16384);
            tma2d(SM_KV + s * 16384, &mp.kvb, 0, (g & 15) * 128, B_KVFULL + s * 8);
          }
        }
      } else {
#pragma unroll 1
        for (int u = 0; u < 6; u++) {
          const int p = u >> 1, a = u & 1;
          mbar_wait_wd(B_OSTORE + a * 8, p & 1);
          if (elect_one()) {
            tma_store2d(&mp.obS, (p < 2 ? a : 2) * 256 + j * 32, i * 128 + (p < 2 ? hf ^ p : a) * 64, SM_Q + (6 - 2 * p + a) * 4096);
            bulk_commit();
            bulk_wait();
            if (a && p) cnt_add(gs->flags + c_row(i, p + 1));
            if (u == 5) mbar_arrive(B_QFREE);
          }
        }
      }
      const int M = warp & 1;
      mbar_wait_wd(B_OLAST + M * 8, 0);
      if (elect_one()) {
        tma_store2d(&mp.obS, 768 + j * 32, i * 128 + M * 64, SM_Q + M * 4096);
        bulk_commit();
        bulk_wait();
        cnt_add(gs->flags + c_row(i, 4 + M));
      }
      __syncwarp();
      TLREC(35 - 3 * M);
      mbar_wait_wd(B_KVEMPTY + (3 - 2 * M) * 8, 1);
      cnt_wait(gs->flags + c_row(i, 4 + M), 8);
      fence_async_gmem();
      if (elect_one()) {
        mbar_expect(B_FX + M * 8, 32768);
        tma3d(SM_KV + (1 - M) * 32768, &mp.obH, 0, i * 128 + M * 64, 12, B_FX + M * 8);
      }
      TLREC(28 - 3 * M);
    }
    if (warp == 2) {
      mbar_wait_wd(B_END, 0);
    } else {
      mbar_arrive_if(B_END, lane == 0);
    }
  } else if (warp < 8) {
    asm volatile("setmaxnreg.inc.sync.aligned.u32 %0;" ::"n"(REG_G));
    const uint32_t tid = threadIdx.x & 127;
    const bool leader = tid == 0;
    const uint32_t row = (tid >> 5) * 16 + (tid & 15);
    const uint32_t sts = row * 128 + ((((tid >> 4) & 1) ^ (tid & 7)) << 4);
    float a0[64], a1[64];
    {
      float a2[32];
      fresh(a0); fresh(a2);
      mbar_wait(B_FULL, 0);
      TLREC(10);
#pragma unroll 1
      for (uint32_t n = 0; n < 16; n++) {
        const uint32_t x = (SM_R >> 4) + (n & 3) * 2048, w = x + 1024, nn = min(n + 1, 15u);
        wg_fence();
#pragma unroll
        for (int kk = 0; kk < 4; kk++) {
          wgmma_ss_n128<0, 1>(a0, desc(x + 512 - hf * 512 + kk * 2), desc(w + kk * 128), kk > 0 || n > 0);
          if (QBW == 2) { wg_commit(); wg_wait<1>(); }
          wgmma_ss_n64<0, 1>(a2, desc(x + hf * 512 + kk * 2), desc(w + 512 + kk * 128), kk > 0 || n > 0);
          wg_commit();
          if (kk == 3) mbar_wait(B_FULL + (nn & 3) * 8, (nn >> 2) & 1);
          wg_wait<QBW ? 1 : 0>();
          if (QBW && kk == 0) mbar_arrive_if(B_EMPTY + ((n - 1) & 3) * 8, leader && n > 0);
        }
        if (!QBW) mbar_arrive_if(B_EMPTY + (n & 3) * 8, leader);
      }
      if (QBW) { wg_wait<0>(); mbar_arrive_if(B_EMPTY + 3 * 8, leader); }
      pin(a0); pin(a2);
      TLREC(46);
      const uint32_t qa = SM_Q + row * 64 + ((((tid >> 4) & 1) ^ ((tid >> 1) & 3)) << 4), qb = qa - hf * 4096, qc = qa + hf * 4096;
      uint32_t m = 0;
      q_block(a0, qa + 4 * 4096, m);
      q_block(a0 + 16, qa + 5 * 4096, m);
      q_block(a0 + 32, qb + 3 * 4096, m);
      q_block(a0 + 48, qb + 4096, m);
      q_block(a2, qc + 2 * 4096, m);
      q_block(a2 + 16, qc, m);
      fence_async_smem();
      if (bound_exceeded(q_bound(m))) sts32(SM_UNSAFE, 1);
      mbar_arrive(B_QRDY);
      TLREC(47);
    }
#pragma unroll 1
    for (int t = 0; t < 2; t++) {
      gemm_tile<true>(a0, a1, 16 + t * 16, 16, leader);
      TLREC(11 + 2 * t);
      constexpr uint32_t xs = SM_R + 3 * 32768;
      bar_sync<1, 128>();
#pragma unroll
      for (int g = 0; g < 8; g++) stsm8f(xs + (g >> 2) * 9216 + (sts ^ ((g & 3) << 5)), a1 + 8 * g);
      asm volatile("st.shared.v4.u32 [%0],{%1,%1,%1,%1};" ::"r"(xs + 8192 + (tid >> 6) * 8192 + tid * 16), "r"(0x3f803f80u) : "memory");
      fence_async_smem();
      uint32_t p[32];
#pragma unroll
      for (int g = 0; g < 32; g++) p[g] = phi2(a0[2 * g], a0[2 * g + 1]);
      pin(p);
      bar_sync<1, 128>();
      float D[36];
      wg_fence();
      wgmma_rs_n72_z<0>(D, p[0], p[1], p[2], p[3], desc(xs >> 4));
#pragma unroll
      for (int kk = 1; kk < 8; kk++)
        wgmma_rs_n72<0>(D, p[4 * kk], p[4 * kk + 1], p[4 * kk + 2], p[4 * kk + 3], desc((xs >> 4) + (kk >> 2) * 576 + (kk & 3) * 2), 1);
      wg_commit();
      const int slot = (2 * j + t) * 16 + i;
      float* zp = gs->zpart + slot * 64 + (tid >> 5) * 16 + ((tid & 31) >> 2);
      float4* pp = gs->part + slot * 512 + tid;
      wg_wait<0>();
      pin(D);
      mbar_arrive_if(B_EMPTY + 3 * 8, leader);
      if ((tid & 3) == 0) { zp[0] = D[32]; zp[8] = D[34]; }
#pragma unroll
      for (int q = 0; q < 4; q++) {
        if (tid < 64) pp[q * 128] = make_float4(D[4 * q], D[4 * q + 1], D[4 * q + 2], D[4 * q + 3]);
        else pp[q * 128] = make_float4(D[16 + 4 * q], D[17 + 4 * q], D[18 + 4 * q], D[19 + 4 * q]);
      }
      mbar_arrive(B_GPART);
      TLREC(12 + 2 * t);
    }
#pragma unroll 1
    for (int t = 0;; t++) {
      gemm_tile<false>(a0, a1, t == 0 ? 48 : 49 + t * 16, t == 2 ? 12 : 16, leader);
      if (t == 2) break;
      TLREC(15 + t * 25);
      bar_sync<1, 128>();
      if (t == 1) mbar_wait(B_QFREE, 0);
      const uint32_t stg = (t == 0 ? SM_R + 3 * 32768 : SM_Q) + sts, stg0 = t == 0 ? stg : SM_R + sts;
#pragma unroll
      for (int g = 0; g < 8; g++) stsm8f(((g < 4 ? stg0 : stg) ^ ((g & 3) << 5)) + (g >> 2) * 16384, a0 + 8 * g);
#pragma unroll
      for (int g = 0; g < 8; g++) stsm8f((stg ^ ((g & 3) << 5)) + 8192 + (g >> 2) * 16384, a1 + 8 * g);
      if (t == 0) {
        mbar_wait(B_FULL, 0);
#pragma unroll 1
        for (int r = 0; r < 4; r++) {
          uint32_t p0[8], p1[8];
          float D0[20], D1[20];
          const uint32_t dst = stg + r * 8192, kv = (SM_R >> 4) + (r >> 1) * 512;
          load_q(p0, dst);
          load_q(p1, dst ^ 64);
#pragma unroll
          for (int g = 0; g < 8; g++) p0[g] = phi2p(p0[g]);
          lin_mma(D0, p0, kv);
#pragma unroll
          for (int g = 0; g < 8; g++) p1[g] = phi2p(p1[g]);
          lin_mma(D1, p1, kv + 256);
          wg_wait<1>();
          lin_out(D0, dst);
          wg_wait<0>();
          lin_out(D1, dst ^ 64);
          fence_async_smem();
          mbar_arrive(B_GSTORE + r * 8);
        }
        mbar_arrive_if(B_EMPTY, leader);
      } else {
        fence_async_smem();
        mbar_arrive(B_GSTORE);
      }
      TLREC(17 + t * 24);
    }
    TLREC(49);
    mbar_wait(B_FULL + 8, 1);
    mbar_wait(B_FULL + 16, 1);
    mbar_wait(B_FX + 8, 0);
    final_mma<1>(a1, 0, 8);
    mbar_wait(B_FX, 0);
    final_mma<0>(a0, 0, 3);
    wg_wait<1>();
    pin(a1);
    final_out<1, 0, 1>(a1, sts, &mp.st[1], i, j, warp == 4);
    final_mma<0>(a0, 3, 8);
    wg_wait<0>();
    TLREC(42);
    pin(a0);
    final_out<0, 0, 0>(a0, sts, &mp.st[1], i, j, warp == 4);
    final_out<0, 1, 1>(a0, sts, &mp.st[1], i, j, warp == 4);
    TLREC(43);
    bulk_wait();
    mbar_arrive_if(B_END, lane == 0);
  } else {
    asm volatile("setmaxnreg.inc.sync.aligned.u32 %0;" ::"n"(REG_A));
    const uint32_t a = (warp >> 2) - 2;
    const uint32_t tid = threadIdx.x & 127;
    const bool leader = tid == 0;
    const uint32_t row = (tid >> 5) * 16 + (tid & 15);
    const uint32_t qoff = row * 64 + ((((tid >> 4) & 1) ^ ((tid >> 1) & 3)) << 4);
    if (a == 0) {
      float acc[32];
      fresh(acc);
#pragma unroll 1
      for (uint32_t st = 0; st < 8; st++) {
        const uint32_t x = (SB >> 4) + st * 1024, w = head_wq(st) >> 4;
        mbar_wait(st == 0 ? B_HX : B_KVSENT, 0);
        mbar_wait(B_HW + st * 8, 0);
        wg_fence();
#pragma unroll
        for (int kk = 0; kk < 8; kk++) wgmma_ss_n64<0, 1>(acc, desc(x + (kk >> 2) * 512 + (kk & 3) * 2), desc(w + kk * 128), kk > 0 || st > 0);
        wg_commit();
        if (st < 2) {
          wg_wait<0>();
          mbar_arrive_if(B_HT - st * 32, leader);
        }
      }
      wg_wait<0>();
      pin(acc);
      mbar_arrive_if(B_HD0, leader);
      TLREC(51);
      uint32_t m = 0;
      q_block(acc, SM_Q + 6 * 4096 + qoff, m);
      q_block(acc + 16, SM_Q + 7 * 4096 + qoff, m);
      m = __reduce_max_sync(~0u, __float_as_uint(q_bound(m)));
      sts32(SM_WMAX + 16 + (tid >> 5) * 4, m);
      fence_async_smem();
    } else {
      float acc[8];
      uint32_t* flagp = gs->flags + F_KVB + (i * 2 + hf) * 4 + (j & 3);
      fresh(acc);
      mbar_wait(B_HK, 0);
      TLREC(9);
      {
        const uint32_t ad = SM_KV + (tid >> 3) * 1024 + 512 + ((tid >> 1) & 3) * 128 + ((((j & 1) * 2 + (tid & 1)) ^ ((tid >> 1) & 3)) << 4) + (tid & 2) * 32;
        uint4 u[8];
#pragma unroll
        for (int e = 0; e < 8; e++)
          asm volatile("ld.shared.v4.u32 {%0,%1,%2,%3},[%4];" : "=r"(u[e].x), "=r"(u[e].y), "=r"(u[e].z), "=r"(u[e].w) : "r"((ad ^ ((e & 1) * 64)) + (e >> 1) * 16384) : "memory");
#pragma unroll
        for (int e = 0; e < 8; e++)
          asm volatile("st.shared.v4.u32 [%4],{%0,%1,%2,%3};" ::"r"(u[e].x), "r"(u[e].y), "r"(u[e].z), "r"(u[e].w), "r"((ad ^ (64 - (e & 1) * 64)) + (e >> 1) * 16384) : "memory");
      }
      fence_async_smem();
      bar_sync<3, 128>();
      TLREC(1);
#pragma unroll 1
      for (uint32_t st = 0; st < 8; st++) {
        const uint32_t x = (SB >> 4) + st * 1024, w = (SM_KV >> 4) + st * 512 + (j & 1) * 2;
        mbar_wait(B_HX + st * 8, 0);
        wg_fence();
#pragma unroll
        for (int kk = 0; kk < 8; kk++) wgmma_ss_n16<0, 1>(acc, desc(x + (kk >> 2) * 512 + (kk & 3) * 2), mkdesc(w + kk * 64, 16, 512, 2), kk > 0 || st > 0);
        wg_commit();
        wg_wait<1>();
        mbar_arrive_if(B_HT - (st / 3) * 8, leader && ((0x52u >> st) & 1));
      }
      wg_wait<0>();
      pin(acc);
      mbar_arrive_if(B_HD1, leader);
      TLREC(2);
      const float c = (j & 2) ? 1.f : 0.17677669529663687f * 1.4426950408889634f;
#pragma unroll
      for (int e = 0; e < 8; e++) acc[e] *= c;
      constexpr uint32_t stg = SM_Q + 4 * 4096;
      stsm8f(stg + row * 32 + (tid & 16), acc);
      fence_async_smem();
      const float n0 = quad_sum(acc[0] * acc[0] + acc[1] * acc[1] + acc[4] * acc[4] + acc[5] * acc[5]);
      const float n1 = quad_sum(acc[2] * acc[2] + acc[3] * acc[3] + acc[6] * acc[6] + acc[7] * acc[7]);
      sts32(SM_WMAX + (tid >> 5) * 4, __reduce_max_sync(~0u, max(__float_as_uint(n0), __float_as_uint(n1))));
      bar_sync<3, 128>();
      if (warp == 12 && elect_one()) {
        tma_store2d(&mp.kvS, (j & 3) * 16, i * 128 + hf * 64, stg);
        bulk_commit();
        const uint32_t m = lds_max4(SM_WMAX) | 1u;
        bulk_wait();
        TLREC(50);
        mbar_arrive(B_KVSENT);
        asm volatile("st.release.gpu.global.u32 [%0],%1;" ::"l"(flagp), "r"(m) : "memory");
        TLREC(3);
      }
      __syncwarp();
    }
    bar_sync<2, 256>();
    const uint32_t qm = lds_max4(SM_WMAX + 16);
    const uint32_t qtop = SM_Q + (6 + a) * 4096 + qoff, kv16 = SM_KV >> 4, obar = B_OSTORE + a * 8;
    float O[16], S0[32], l0 = 0.f, l1 = 0.f;
    uint32_t q[8];
    load_q(q, qtop);
    mbar_wait(B_KVFULL, 0);
    wg_fence();
    wgmma_rs_n64_z<0>(S0, q[0], q[1], q[2], q[3], desc(kv16));
    wgmma_rs_n64<0>(S0, q[4], q[5], q[6], q[7], desc(kv16 + 2), 1);
    wg_commit();
    wg_wait<0>();
    pin(S0);
    mbar_wait(B_KINFO, 0);
    uint32_t pass = 0;
    if (__shfl_sync(~0u, (uint32_t)bound_exceeded(__uint_as_float(qm)), 0) == 0) {
      float S1[32];
      uint32_t P0[16], P1[16];
#pragma unroll
      for (int e = 0; e < 16; e++) { O[e] = 0.f; P1[e] = 0; }
      pin(O); pin(P1);
      uint32_t bend = 64 / UNR;
      if (a == 0) TLREC(29);
#pragma unroll 1
      for (uint32_t b = 0; b < bend; b++) {
        const uint32_t g = b * UNR;
        if (g == 12) {
          mbar_wait(B_QRDY, 0);
          if (__shfl_sync(~0u, lds32(SM_UNSAFE), 0)) bend = 16 / UNR;
        }
#pragma unroll
        for (int u = 0; u < UNR; u++) {
          const uint32_t gn = u < UNR - 1 ? g + u + 1 : min(g + u + 1, 63u);
          const uint32_t cur = kv16 + ((g + u) & 3) * 1024, prv = kv16 + ((g + u + 3) & 3) * 1024, nxt = kv16 + ((g + u + 1) & 3) * 1024;
          const uint32_t fb = B_KVFULL + (gn & 3) * 8, fp = (gn >> 2) & 1, eb = B_KVEMPTY + ((g + u + 3) & 3) * 8;
          if (u == 0 && (g & 15) == 0 && g > 0) {
            float r0 = l0, r1 = l1;
            l0 = 0.f; l1 = 0.f;
            attn_batch(S1, q, kv16 + 512, O, P1, kv16 + 3 * 1024 + 512, 1);
            const uint32_t ok = mbar_test(B_KVFULL + 8, 0);
            r0 = rcp(quad_sum(r0)); r1 = rcp(quad_sum(r1));
            attn_exp(S0, P0, l0, l1, never, S1, O);
            mbar_arrive_if(B_KVEMPTY + 3 * 8, leader);
            if (__builtin_expect(!ok, 0)) mbar_wait(B_KVFULL + 8, 0);
            const uint32_t oa = qtop + 8192 - g * 512;
            stsm8s(oa, O, r0, r1);
            stsm8s(oa ^ 32, O + 8, r0, r1);
            attn_batch(S0, q, kv16 + 1024, O, P0, kv16, 0);
            fence_async_smem();
            mbar_arrive(obar);
            attn_exp(S1, P1, l0, l1, never, S0, O);
          } else {
            attn_batch(S1, q, cur + 512, O, P1, prv + 512, 1);
            const uint32_t ok = mbar_test(fb, fp);
            attn_exp(S0, P0, l0, l1, never, S1, O);
            mbar_arrive_if(eb, leader && (u > 0 || g > 0));
            if (u == UNR - 1) {
              if (__builtin_expect(!ok || (gn & 15) == 0, 0)) {
                mbar_wait(fb, fp);
                load_q(q, qtop - (gn >> 4) * 8192);
              }
            } else if (__builtin_expect(!ok, 0)) mbar_wait(fb, fp);
            attn_batch(S0, q, nxt, O, P0, cur, u > 0 || g > 0);
            attn_exp(S1, P1, l0, l1, never, S0, O);
          }
        }
      }
      wg_fence();
#pragma unroll
      for (int kk = 0; kk < 4; kk++)
        wgmma_rs_n32<1>(O, P1[4 * kk], P1[4 * kk + 1], P1[4 * kk + 2], P1[4 * kk + 3], desc(kv16 + 3 * 1024 + 512 + 4 + kk * 128), 1);
      wg_commit();
      wg_wait<0>();
      pin(O);
      mbar_arrive_if(B_KVEMPTY + 3 * 8, leader);
      pass = bend * UNR / 16;
      attn_finish(O, l0, l1, qtop + 8192 - pass * 8192, pass == 4 ? obar + 16 : obar);
    }
    if (pass < 4) attn_general(pass, qtop, a);
    TLREC(44 + a);
    mbar_arrive_if(B_END, lane == 0);
  }
}

typedef CUresult (*EncodeFn)(CUtensorMap*, CUtensorMapDataType, cuuint32_t, void*, const cuuint64_t*, const cuuint64_t*, const cuuint32_t*,
                             const cuuint32_t*, CUtensorMapInterleave, CUtensorMapSwizzle, CUtensorMapL2promotion, CUtensorMapFloatOOBfill);

struct Dim { uint64_t size, stride; uint32_t box; };
template <int N>
void mapnd(EncodeFn enc, CUtensorMap* m, const void* p, const Dim (&d)[N], CUtensorMapSwizzle sw = CU_TENSOR_MAP_SWIZZLE_128B) {
  cuuint64_t gd[N], gs[N];
  cuuint32_t bd[N], es[N];
  for (int k = 0; k < N; k++) { gd[k] = d[k].size; gs[k] = d[k].stride * 2; bd[k] = d[k].box; es[k] = 1; }
  enc(m, CU_TENSOR_MAP_DATA_TYPE_BFLOAT16, N, (void*)p, gd, gs + 1, bd, es, CU_TENSOR_MAP_INTERLEAVE_NONE, sw,
      CU_TENSOR_MAP_L2_PROMOTION_L2_128B, CU_TENSOR_MAP_FLOAT_OOB_FILL_NONE);
}

}

extern "C" void kernel_launch(void* const* d_in, const int* in_sizes, int n_in, void* d_out, int out_size) {
  (void)in_sizes; (void)n_in; (void)out_size;
  EncodeFn enc = nullptr;
  cudaDriverEntryPointQueryResult qr;
  cudaGetDriverEntryPoint("cuTensorMapEncodeTiled", (void**)&enc, cudaEnableDefault, &qr);
  void *sm, *oa, *ob;
  cudaGetSymbolAddress(&sm, g_s);
  cudaGetSymbolAddress(&oa, g_oa);
  cudaGetSymbolAddress(&ob, g_ob);
  void* kvb = ((Small*)sm)->kvb;
  const void *xA = d_in[0], *wqkv = d_in[1], *woA = d_in[2], *xB = d_in[3], *wq = d_in[4], *wk = d_in[5], *wv = d_in[6], *woB = d_in[7];
  Maps mp;
  mapnd<3>(enc, &mp.xBh, xB, {{64, 1, 64}, {2048, 1024, 64}, {16, 64, 2}});
  mapnd<2>(enc, &mp.wqh, wq, {{1024, 1, 64}, {1024, 1024, 128}});
  mapnd<2>(enc, &mp.wkv[0], wk, {{64, 1, 64}, {512, 64, 256}});
  mapnd<2>(enc, &mp.wkv[1], wv, {{64, 1, 64}, {512, 64, 256}});
  mapnd<2>(enc, &mp.kvS, kvb, {{64, 1, 16}, {2048, 64, 64}}, CU_TENSOR_MAP_SWIZZLE_NONE);
  mapnd<2>(enc, &mp.kvb, kvb, {{64, 1, 64}, {2048, 64, 128}});
  mapnd<2>(enc, &mp.x[0], xB, {{1024, 1, 64}, {2048, 1024, 128}});
  mapnd<2>(enc, &mp.x[1], xA, {{1024, 1, 64}, {2048, 1024, 128}});
  mapnd<3>(enc, &mp.w[0], wq, {{64, 1, 64}, {1024, 1024, 64}, {16, 64, 2}});
  mapnd<3>(enc, &mp.w[1], wqkv, {{1024, 1, 64}, {1024, 3072, 64}, {3, 1024, 2}});
  mapnd<3>(enc, &mp.w[2], wqkv, {{64, 1, 64}, {1024, 3072, 64}, {48, 64, 2}});
  mapnd<2>(enc, &mp.oL[0], oa, {{1024, 1, 64}, {2048, 1024, 128}});
  mapnd<2>(enc, &mp.oL[1], ob, {{1024, 1, 64}, {2048, 1024, 128}});
  mapnd<5>(enc, &mp.wo[0], woA, {{64, 1, 64}, {32, 1024, 32}, {4, 256 * 1024, 1}, {8, 32 * 1024, 2}, {16, 64, 2}});
  mapnd<5>(enc, &mp.wo[1], woB, {{64, 1, 64}, {32, 1024, 32}, {4, 32 * 1024, 1}, {8, 128 * 1024, 2}, {16, 64, 2}});
  mapnd<2>(enc, &mp.st[0], oa, {{1024, 1, 64}, {2048, 1024, 64}});
  mapnd<2>(enc, &mp.st[1], d_out, {{2048, 1, 64}, {2048, 2048, 64}});
  mapnd<3>(enc, &mp.obH, ob, {{64, 1, 64}, {2048, 1024, 64}, {16, 64, 4}});
  mapnd<2>(enc, &mp.obS, ob, {{1024, 1, 32}, {2048, 1024, 64}}, CU_TENSOR_MAP_SWIZZLE_64B);
  cudaFuncSetAttribute(fused_kernel, cudaFuncAttributeMaxDynamicSharedMemorySize, SMEM_BYTES);
  fused_kernel<<<128, 512, SMEM_BYTES, cudaStreamPerThread>>>(0, (Small*)sm, mp);
}
```

```cpp
#include <cuda_runtime.h>
#include <cuda_bf16.h>
#include <cuda.h>
#include <stdint.h>

namespace {

template<int TB> __device__ __forceinline__ void wgmma_rs_n32(float (&d)[16], uint32_t a0, uint32_t a1, uint32_t a2, uint32_t a3, uint64_t db, int sc){
  asm volatile("{\n.reg .pred p;\nsetp.ne.b32 p, %21, 0;\n"
  "wgmma.mma_async.sync.aligned.m64n32k16.f32.bf16.bf16 {%0,%1,%2,%3,%4,%5,%6,%7,%8,%9,%10,%11,%12,%13,%14,%15}, {%16,%17,%18,%19}, %20, p, 1, 1, %22;\n}\n"
  : "+f"(d[0]),"+f"(d[1]),"+f"(d[2]),"+f"(d[3]),"+f"(d[4]),"+f"(d[5]),"+f"(d[6]),"+f"(d[7]),
    "+f"(d[8]),"+f"(d[9]),"+f"(d[10]),"+f"(d[11]),"+f"(d[12]),"+f"(d[13]),"+f"(d[14]),"+f"(d[15])
  : "r"(a0), "r"(a1), "r"(a2), "r"(a3), "l"(db), "r"(sc), "n"(TB));
}
template<int TB> __device__ __forceinline__ void wgmma_rs_n40(float (&d)[20], uint32_t a0, uint32_t a1, uint32_t a2, uint32_t a3, uint64_t db, int sc){
  asm volatile("{\n.reg .pred p;\nsetp.ne.b32 p, %25, 0;\n"
  "wgmma.mma_async.sync.aligned.m64n40k16.f32.bf16.bf16 {%0,%1,%2,%3,%4,%5,%6,%7,%8,%9,%10,%11,%12,%13,%14,%15,%16,%17,%18,%19}, {%20,%21,%22,%23}, %24, p, 1, 1, %26;\n}\n"
  : "+f"(d[0]),"+f"(d[1]),"+f"(d[2]),"+f"(d[3]),"+f"(d[4]),"+f"(d[5]),"+f"(d[6]),"+f"(d[7]),
    "+f"(d[8]),"+f"(d[9]),"+f"(d[10]),"+f"(d[11]),"+f"(d[12]),"+f"(d[13]),"+f"(d[14]),"+f"(d[15]),
    "+f"(d[16]),"+f"(d[17]),"+f"(d[18]),"+f"(d[19])
  : "r"(a0), "r"(a1), "r"(a2), "r"(a3), "l"(db), "r"(sc), "n"(TB));
}
template<int TB> __device__ __forceinline__ void wgmma_rs_n40_z(float (&d)[20], uint32_t a0, uint32_t a1, uint32_t a2, uint32_t a3, uint64_t db){
  asm volatile("wgmma.mma_async.sync.aligned.m64n40k16.f32.bf16.bf16 {%0,%1,%2,%3,%4,%5,%6,%7,%8,%9,%10,%11,%12,%13,%14,%15,%16,%17,%18,%19}, {%20,%21,%22,%23}, %24, 0, 1, 1, %25;\n"
  : "=f"(d[0]),"=f"(d[1]),"=f"(d[2]),"=f"(d[3]),"=f"(d[4]),"=f"(d[5]),"=f"(d[6]),"=f"(d[7]),
    "=f"(d[8]),"=f"(d[9]),"=f"(d[10]),"=f"(d[11]),"=f"(d[12]),"=f"(d[13]),"=f"(d[14]),"=f"(d[15]),
    "=f"(d[16]),"=f"(d[17]),"=f"(d[18]),"=f"(d[19])
  : "r"(a0), "r"(a1), "r"(a2), "r"(a3), "l"(db), "n"(TB));
}
template<int TB> __device__ __forceinline__ void wgmma_rs_n64(float (&d)[32], uint32_t a0, uint32_t a1, uint32_t a2, uint32_t a3, uint64_t db, int sc){
  asm volatile("{\n.reg .pred p;\nsetp.ne.b32 p, %37, 0;\n"
  "wgmma.mma_async.sync.aligned.m64n64k16.f32.bf16.bf16 {%0,%1,%2,%3,%4,%5,%6,%7,%8,%9,%10,%11,%12,%13,%14,%15,%16,%17,%18,%19,%20,%21,%22,%23,%24,%25,%26,%27,%28,%29,%30,%31}, {%32,%33,%34,%35}, %36, p, 1, 1, %38;\n}\n"
  : "+f"(d[0]),"+f"(d[1]),"+f"(d[2]),"+f"(d[3]),"+f"(d[4]),"+f"(d[5]),"+f"(d[6]),"+f"(d[7]),
    "+f"(d[8]),"+f"(d[9]),"+f"(d[10]),"+f"(d[11]),"+f"(d[12]),"+f"(d[13]),"+f"(d[14]),"+f"(d[15]),
    "+f"(d[16]),"+f"(d[17]),"+f"(d[18]),"+f"(d[19]),"+f"(d[20]),"+f"(d[21]),"+f"(d[22]),"+f"(d[23]),
    "+f"(d[24]),"+f"(d[25]),"+f"(d[26]),"+f"(d[27]),"+f"(d[28]),"+f"(d[29]),"+f"(d[30]),"+f"(d[31])
  : "r"(a0), "r"(a1), "r"(a2), "r"(a3), "l"(db), "r"(sc), "n"(TB));
}
template<int TB> __device__ __forceinline__ void wgmma_rs_n64_z(float (&d)[32], uint32_t a0, uint32_t a1, uint32_t a2, uint32_t a3, uint64_t db){
  asm volatile("wgmma.mma_async.sync.aligned.m64n64k16.f32.bf16.bf16 {%0,%1,%2,%3,%4,%5,%6,%7,%8,%9,%10,%11,%12,%13,%14,%15,%16,%17,%18,%19,%20,%21,%22,%23,%24,%25,%26,%27,%28,%29,%30,%31}, {%32,%33,%34,%35}, %36, 0, 1, 1, %37;\n"
  : "=f"(d[0]),"=f"(d[1]),"=f"(d[2]),"=f"(d[3]),"=f"(d[4]),"=f"(d[5]),"=f"(d[6]),"=f"(d[7]),
    "=f"(d[8]),"=f"(d[9]),"=f"(d[10]),"=f"(d[11]),"=f"(d[12]),"=f"(d[13]),"=f"(d[14]),"=f"(d[15]),
    "=f"(d[16]),"=f"(d[17]),"=f"(d[18]),"=f"(d[19]),"=f"(d[20]),"=f"(d[21]),"=f"(d[22]),"=f"(d[23]),
    "=f"(d[24]),"=f"(d[25]),"=f"(d[26]),"=f"(d[27]),"=f"(d[28]),"=f"(d[29]),"=f"(d[30]),"=f"(d[31])
  : "r"(a0), "r"(a1), "r"(a2), "r"(a3), "l"(db), "n"(TB));
}
template<int TB> __device__ __forceinline__ void wgmma_rs_n72(float (&d)[36], uint32_t a0, uint32_t a1, uint32_t a2, uint32_t a3, uint64_t db, int sc){
  asm volatile("{\n.reg .pred p;\nsetp.ne.b32 p, %41, 0;\n"
  "wgmma.mma_async.sync.aligned.m64n72k16.f32.bf16.bf16 {%0,%1,%2,%3,%4,%5,%6,%7,%8,%9,%10,%11,%12,%13,%14,%15,%16,%17,%18,%19,%20,%21,%22,%23,%24,%25,%26,%27,%28,%29,%30,%31,%32,%33,%34,%35}, {%36,%37,%38,%39}, %40, p, 1, 1, %42;\n}\n"
  : "+f"(d[0]),"+f"(d[1]),"+f"(d[2]),"+f"(d[3]),"+f"(d[4]),"+f"(d[5]),"+f"(d[6]),"+f"(d[7]),
    "+f"(d[8]),"+f"(d[9]),"+f"(d[10]),"+f"(d[11]),"+f"(d[12]),"+f"(d[13]),"+f"(d[14]),"+f"(d[15]),
    "+f"(d[16]),"+f"(d[17]),"+f"(d[18]),"+f"(d[19]),"+f"(d[20]),"+f"(d[21]),"+f"(d[22]),"+f"(d[23]),
    "+f"(d[24]),"+f"(d[25]),"+f"(d[26]),"+f"(d[27]),"+f"(d[28]),"+f"(d[29]),"+f"(d[30]),"+f"(d[31]),
    "+f"(d[32]),"+f"(d[33]),"+f"(d[34]),"+f"(d[35])
  : "r"(a0), "r"(a1), "r"(a2), "r"(a3), "l"(db), "r"(sc), "n"(TB));
}
template<int TB> __device__ __forceinline__ void wgmma_rs_n72_z(float (&d)[36], uint32_t a0, uint32_t a1, uint32_t a2, uint32_t a3, uint64_t db){
  asm volatile("wgmma.mma_async.sync.aligned.m64n72k16.f32.bf16.bf16 {%0,%1,%2,%3,%4,%5,%6,%7,%8,%9,%10,%11,%12,%13,%14,%15,%16,%17,%18,%19,%20,%21,%22,%23,%24,%25,%26,%27,%28,%29,%30,%31,%32,%33,%34,%35}, {%36,%37,%38,%39}, %40, 0, 1, 1, %41;\n"
  : "=f"(d[0]),"=f"(d[1]),"=f"(d[2]),"=f"(d[3]),"=f"(d[4]),"=f"(d[5]),"=f"(d[6]),"=f"(d[7]),
    "=f"(d[8]),"=f"(d[9]),"=f"(d[10]),"=f"(d[11]),"=f"(d[12]),"=f"(d[13]),"=f"(d[14]),"=f"(d[15]),
    "=f"(d[16]),"=f"(d[17]),"=f"(d[18]),"=f"(d[19]),"=f"(d[20]),"=f"(d[21]),"=f"(d[22]),"=f"(d[23]),
    "=f"(d[24]),"=f"(d[25]),"=f"(d[26]),"=f"(d[27]),"=f"(d[28]),"=f"(d[29]),"=f"(d[30]),"=f"(d[31]),
    "=f"(d[32]),"=f"(d[33]),"=f"(d[34]),"=f"(d[35])
  : "r"(a0), "r"(a1), "r"(a2), "r"(a3), "l"(db), "n"(TB));
}
template<int TA,int TB> __device__ __forceinline__ void wgmma_ss_n128(float (&d)[64], uint64_t da, uint64_t db, int sc){
  asm volatile("{\n.reg .pred p;\nsetp.ne.b32 p, %66, 0;\n"
  "wgmma.mma_async.sync.aligned.m64n128k16.f32.bf16.bf16 {%0,%1,%2,%3,%4,%5,%6,%7,%8,%9,%10,%11,%12,%13,%14,%15,%16,%17,%18,%19,%20,%21,%22,%23,%24,%25,%26,%27,%28,%29,%30,%31,%32,%33,%34,%35,%36,%37,%38,%39,%40,%41,%42,%43,%44,%45,%46,%47,%48,%49,%50,%51,%52,%53,%54,%55,%56,%57,%58,%59,%60,%61,%62,%63}, %64, %65, p, 1, 1, %67, %68;\n}\n"
  : "+f"(d[0]),"+f"(d[1]),"+f"(d[2]),"+f"(d[3]),"+f"(d[4]),"+f"(d[5]),"+f"(d[6]),"+f"(d[7]),
    "+f"(d[8]),"+f"(d[9]),"+f"(d[10]),"+f"(d[11]),"+f"(d[12]),"+f"(d[13]),"+f"(d[14]),"+f"(d[15]),
    "+f"(d[16]),"+f"(d[17]),"+f"(d[18]),"+f"(d[19]),"+f"(d[20]),"+f"(d[21]),"+f"(d[22]),"+f"(d[23]),
    "+f"(d[24]),"+f"(d[25]),"+f"(d[26]),"+f"(d[27]),"+f"(d[28]),"+f"(d[29]),"+f"(d[30]),"+f"(d[31]),
    "+f"(d[32]),"+f"(d[33]),"+f"(d[34]),"+f"(d[35]),"+f"(d[36]),"+f"(d[37]),"+f"(d[38]),"+f"(d[39]),
    "+f"(d[40]),"+f"(d[41]),"+f"(d[42]),"+f"(d[43]),"+f"(d[44]),"+f"(d[45]),"+f"(d[46]),"+f"(d[47]),
    "+f"(d[48]),"+f"(d[49]),"+f"(d[50]),"+f"(d[51]),"+f"(d[52]),"+f"(d[53]),"+f"(d[54]),"+f"(d[55]),
    "+f"(d[56]),"+f"(d[57]),"+f"(d[58]),"+f"(d[59]),"+f"(d[60]),"+f"(d[61]),"+f"(d[62]),"+f"(d[63])
  : "l"(da), "l"(db), "r"(sc), "n"(TA), "n"(TB));
}
template<int TA,int TB> __device__ __forceinline__ void wgmma_ss_n128_z(float (&d)[64], uint64_t da, uint64_t db){
  asm volatile("wgmma.mma_async.sync.aligned.m64n128k16.f32.bf16.bf16 {%0,%1,%2,%3,%4,%5,%6,%7,%8,%9,%10,%11,%12,%13,%14,%15,%16,%17,%18,%19,%20,%21,%22,%23,%24,%25,%26,%27,%28,%29,%30,%31,%32,%33,%34,%35,%36,%37,%38,%39,%40,%41,%42,%43,%44,%45,%46,%47,%48,%49,%50,%51,%52,%53,%54,%55,%56,%57,%58,%59,%60,%61,%62,%63}, %64, %65, 0, 1, 1, %66, %67;\n"
  : "=f"(d[0]),"=f"(d[1]),"=f"(d[2]),"=f"(d[3]),"=f"(d[4]),"=f"(d[5]),"=f"(d[6]),"=f"(d[7]),
    "=f"(d[8]),"=f"(d[9]),"=f"(d[10]),"=f"(d[11]),"=f"(d[12]),"=f"(d[13]),"=f"(d[14]),"=f"(d[15]),
    "=f"(d[16]),"=f"(d[17]),"=f"(d[18]),"=f"(d[19]),"=f"(d[20]),"=f"(d[21]),"=f"(d[22]),"=f"(d[23]),
    "=f"(d[24]),"=f"(d[25]),"=f"(d[26]),"=f"(d[27]),"=f"(d[28]),"=f"(d[29]),"=f"(d[30]),"=f"(d[31]),
    "=f"(d[32]),"=f"(d[33]),"=f"(d[34]),"=f"(d[35]),"=f"(d[36]),"=f"(d[37]),"=f"(d[38]),"=f"(d[39]),
    "=f"(d[40]),"=f"(d[41]),"=f"(d[42]),"=f"(d[43]),"=f"(d[44]),"=f"(d[45]),"=f"(d[46]),"=f"(d[47]),
    "=f"(d[48]),"=f"(d[49]),"=f"(d[50]),"=f"(d[51]),"=f"(d[52]),"=f"(d[53]),"=f"(d[54]),"=f"(d[55]),
    "=f"(d[56]),"=f"(d[57]),"=f"(d[58]),"=f"(d[59]),"=f"(d[60]),"=f"(d[61]),"=f"(d[62]),"=f"(d[63])
  : "l"(da), "l"(db), "n"(TA), "n"(TB));
}
template<int TA,int TB> __device__ __forceinline__ void wgmma_ss_n16(float (&d)[8], uint64_t da, uint64_t db, int sc){
  asm volatile("{\n.reg .pred p;\nsetp.ne.b32 p, %10, 0;\n"
  "wgmma.mma_async.sync.aligned.m64n16k16.f32.bf16.bf16 {%0,%1,%2,%3,%4,%5,%6,%7}, %8, %9, p, 1, 1, %11, %12;\n}\n"
  : "+f"(d[0]),"+f"(d[1]),"+f"(d[2]),"+f"(d[3]),"+f"(d[4]),"+f"(d[5]),"+f"(d[6]),"+f"(d[7])
  : "l"(da), "l"(db), "r"(sc), "n"(TA), "n"(TB));
}
template<int TA,int TB> __device__ __forceinline__ void wgmma_ss_n64(float (&d)[32], uint64_t da, uint64_t db, int sc){
  asm volatile("{\n.reg .pred p;\nsetp.ne.b32 p, %34, 0;\n"
  "wgmma.mma_async.sync.aligned.m64n64k16.f32.bf16.bf16 {%0,%1,%2,%3,%4,%5,%6,%7,%8,%9,%10,%11,%12,%13,%14,%15,%16,%17,%18,%19,%20,%21,%22,%23,%24,%25,%26,%27,%28,%29,%30,%31}, %32, %33, p, 1, 1, %35, %36;\n}\n"
  : "+f"(d[0]),"+f"(d[1]),"+f"(d[2]),"+f"(d[3]),"+f"(d[4]),"+f"(d[5]),"+f"(d[6]),"+f"(d[7]),
    "+f"(d[8]),"+f"(d[9]),"+f"(d[10]),"+f"(d[11]),"+f"(d[12]),"+f"(d[13]),"+f"(d[14]),"+f"(d[15]),
    "+f"(d[16]),"+f"(d[17]),"+f"(d[18]),"+f"(d[19]),"+f"(d[20]),"+f"(d[21]),"+f"(d[22]),"+f"(d[23]),
    "+f"(d[24]),"+f"(d[25]),"+f"(d[26]),"+f"(d[27]),"+f"(d[28]),"+f"(d[29]),"+f"(d[30]),"+f"(d[31])
  : "l"(da), "l"(db), "r"(sc), "n"(TA), "n"(TB));
}


constexpr uint32_t SB     = 1024;
constexpr uint32_t SM_R   = SB;
constexpr uint32_t SM_KV  = SB + 131072;
constexpr uint32_t SM_Q   = SB + 196608;
constexpr uint32_t SM_BAR = SB + 229376;
constexpr uint32_t SMEM_BYTES = 229376 + 1024;
__device__ __forceinline__ uint32_t head_wq(uint32_t st) { return SB + ((0x01BA9C0Cu >> (4 * st)) & 15) * 16384; }
constexpr uint32_t B_HX = SM_BAR, B_HK = SM_BAR + 64, B_HW = SM_BAR + 72;
constexpr uint32_t B_FULL = SM_BAR + 136, B_EMPTY = SM_BAR + 168, B_KVFULL = SM_BAR + 200, B_FX = SM_BAR + 232;
constexpr uint32_t B_HD0 = SM_BAR + 248, B_KINFO = SM_BAR + 256, B_KVSENT = SM_BAR + 264, B_QFREE = SM_BAR + 272;
constexpr uint32_t B_HT = SM_BAR + 312, B_HD1 = B_HT - 24;
constexpr uint32_t B_KVEMPTY = SM_BAR + 320;
constexpr uint32_t B_END = SM_BAR + 352;
constexpr uint32_t B_QRDY = SM_BAR + 360, B_GPART = SM_BAR + 368, B_OSTORE = SM_BAR + 376, B_OLAST = SM_BAR + 392, B_GSTORE = SM_BAR + 408;
constexpr uint32_t SM_WMAX = SM_BAR + 448, SM_KINFO = SM_BAR + 480, SM_UNSAFE = SM_BAR + 484, SM_DUMMY = SM_BAR + 496;

constexpr int F_KVB = 0;
constexpr int F_COL = 128, F_ROW = F_COL + 8 * 32, F_DONE = F_ROW + 16 * 32;
__device__ __forceinline__ int c_part(int j, int t) { return F_COL + j * 32 + t; }
__device__ __forceinline__ int c_red(int j) { return F_COL + j * 32 + 2; }
__device__ __forceinline__ int c_row(int i, int p) { return F_ROW + i * 32 + p; }
struct Small {
  uint32_t flags[1024];
  __nv_bfloat16 kvb[2048 * 64];
  uint32_t blob[8 * 4096];
  float zpart[16 * 16 * 64];
  float4 part[16 * 16 * 512];
};
__device__ __align__(1024) Small g_s;
__device__ __align__(1024) __nv_bfloat16 g_oa[2048 * 1024];
__device__ __align__(1024) __nv_bfloat16 g_ob[2048 * 1024];

struct Maps {
  CUtensorMap xBh, wqh, wkv[2], kvS, kvb;
  CUtensorMap x[2], w[3];
  CUtensorMap oL[2], wo[2], st[2];
  CUtensorMap obH, obS;
};

__device__ __forceinline__ void wg_fence() { asm volatile("wgmma.fence.sync.aligned;" ::: "memory"); }
__device__ __forceinline__ void wg_commit() { asm volatile("wgmma.commit_group.sync.aligned;" ::: "memory"); }
template <int N> __device__ __forceinline__ void wg_wait() { asm volatile("wgmma.wait_group.sync.aligned %0;" ::"n"(N) : "memory"); }
template <int N> __device__ __forceinline__ void pin(float (&d)[N]) {
#pragma unroll
  for (int i = 0; i < N; i++) asm volatile("" : "+f"(d[i])::"memory");
}
template <int N> __device__ __forceinline__ void pin(uint32_t (&d)[N]) {
#pragma unroll
  for (int i = 0; i < N; i++) asm volatile("" : "+r"(d[i])::"memory");
}
template <int N> __device__ __forceinline__ void fresh(float (&d)[N]) {
#pragma unroll
  for (int i = 0; i < N; i++) asm volatile("" : "=f"(d[i]));
}
__device__ __forceinline__ uint64_t mkdesc(uint32_t a16, uint32_t lbo, uint32_t sbo, uint32_t sw) {
  uint32_t lo = a16 + ((lbo >> 4) << 16), hi = (sbo >> 4) | (sw << 30);
  uint64_t d;
  asm("mov.b64 %0,{%1,%2};" : "=l"(d) : "r"(lo), "r"(hi));
  return d;
}
__device__ __forceinline__ uint64_t desc(uint32_t a16) { return mkdesc(a16, 8192, 1024, 1); }

__device__ __forceinline__ float ex2(float x) { float y; asm("ex2.approx.ftz.f32 %0,%1;" : "=f"(y) : "f"(x)); return y; }
__device__ __forceinline__ float rcp(float x) { float y; asm("rcp.approx.ftz.f32 %0,%1;" : "=f"(y) : "f"(x)); return y; }
__device__ __forceinline__ uint32_t pack(float lo, float hi) { uint32_t r; asm("cvt.rn.bf16x2.f32 %0,%1,%2;" : "=r"(r) : "f"(hi), "f"(lo)); return r; }
__device__ __forceinline__ uint32_t phi2(float t0, float t1) {
  const float e0 = __saturatef(ex2(t0 * 1.4426950408889634f) + 1e-6f), e1 = __saturatef(ex2(t1 * 1.4426950408889634f) + 1e-6f);
  uint32_t r;
  asm("cvt.rn.relu.bf16x2.f32 %0,%1,%2;" : "=r"(r) : "f"(t1), "f"(t0));
  asm("add.rn.bf16x2 %0,%0,%1;" : "+r"(r) : "r"(pack(e0, e1)));
  return r;
}
__device__ __forceinline__ uint32_t phi2p(uint32_t t) {
  uint32_t e = pack(ex2(__uint_as_float(t << 16) * 1.4426950408889634f), ex2(__uint_as_float(t & 0xffff0000u) * 1.4426950408889634f));
  asm("min.bf16x2 %0,%0,%1;" : "+r"(e) : "r"(0x3f803f80u));
  asm("max.NaN.bf16x2 %0,%0,%1;" : "+r"(t) : "r"(0x35863586u));
  asm("add.rn.bf16x2 %0,%0,%1;" : "+r"(t) : "r"(e));
  return t;
}

__device__ __forceinline__ void mbar_init(uint32_t b, uint32_t n) { asm volatile("mbarrier.init.shared::cta.b64 [%0],%1;" ::"r"(b), "r"(n) : "memory"); }
__device__ __forceinline__ void mbar_arrive(uint32_t b) { asm volatile("mbarrier.arrive.shared::cta.b64 _,[%0];" ::"r"(b) : "memory"); }
__device__ __forceinline__ void mbar_arrive_if(uint32_t b, bool p) {
  asm volatile("{\n.reg .pred p;\nsetp.ne.u32 p,%1,0;\n@p mbarrier.arrive.shared::cta.b64 _,[%0];\n}" ::"r"(b), "r"((uint32_t)p) : "memory");
}
__device__ __forceinline__ void mbar_expect(uint32_t b, uint32_t bytes) {
  asm volatile("mbarrier.arrive.expect_tx.shared::cta.b64 _,[%0],%1;" ::"r"(b), "r"(bytes) : "memory");
}
__device__ __forceinline__ void mbar_wait_wd(uint32_t b, uint32_t parity) {
  asm volatile(
      "{\n.reg .pred p;\n.reg .u32 t0;\n"
      "mov.u32 t0,0;\n"
      "MW_LOOP:\n"
      "mbarrier.try_wait.parity.shared::cta.b64 p,[%0],%1,100000;\n"
      "@p bra MW_DONE;\n"
      "add.u32 t0,t0,1;\n"
      "setp.lt.u32 p,t0,20000;\n"
      "@p bra MW_LOOP;\n"
      "trap;\n"
      "MW_DONE:\n}" ::"r"(b), "r"(parity) : "memory");
}
__device__ __forceinline__ void mbar_wait(uint32_t b, uint32_t parity) {
  asm volatile("{\n.reg .pred p;\nMS_LOOP:\nmbarrier.try_wait.parity.shared::cta.b64 p,[%0],%1;\n@!p bra MS_LOOP;\n}" ::"r"(b), "r"(parity) : "memory");
}
__device__ __forceinline__ bool elect_one() {
  uint32_t p;
  asm volatile("{\n.reg .pred p;\nelect.sync _|p,0xffffffff;\nselp.u32 %0,1,0,p;\n}" : "=r"(p));
  return p != 0;
}
template <int ID, int N> __device__ __forceinline__ void bar_sync() { asm volatile("bar.sync %0,%1;" ::"n"(ID), "n"(N) : "memory"); }
__device__ __forceinline__ void stage_landed(uint32_t id) { asm volatile("bar.sync %0,160;" ::"r"(id) : "memory"); }
__device__ __forceinline__ void fence_async_smem() { asm volatile("fence.proxy.async.shared::cta;" ::: "memory"); }
__device__ __forceinline__ void fence_async_gmem() { asm volatile("fence.proxy.async.global;" ::: "memory"); }
__device__ __forceinline__ void fence_acquire() { asm volatile("fence.acquire.gpu;" ::: "memory"); }

__device__ __forceinline__ void tma2d(uint32_t dst, const CUtensorMap* m, int c0, int c1, uint32_t bar) {
  asm volatile("cp.async.bulk.tensor.2d.shared::cluster.global.mbarrier::complete_tx::bytes [%0],[%1,{%3,%4}],[%2];"
               ::"r"(dst), "l"(m), "r"(bar), "r"(c0), "r"(c1) : "memory");
}
__device__ __forceinline__ void tma3d(uint32_t dst, const CUtensorMap* m, int c0, int c1, int c2, uint32_t bar) {
  asm volatile("cp.async.bulk.tensor.3d.shared::cluster.global.mbarrier::complete_tx::bytes [%0],[%1,{%3,%4,%5}],[%2];"
               ::"r"(dst), "l"(m), "r"(bar), "r"(c0), "r"(c1), "r"(c2) : "memory");
}
__device__ __forceinline__ void tma5d(uint32_t dst, const CUtensorMap* m, int c2, int c3, int c4, uint32_t bar) {
  asm volatile("cp.async.bulk.tensor.5d.shared::cluster.global.mbarrier::complete_tx::bytes [%0],[%1,{%6,%6,%3,%4,%5}],[%2];"
               ::"r"(dst), "l"(m), "r"(bar), "r"(c2), "r"(c3), "r"(c4), "r"(0) : "memory");
}
__device__ __forceinline__ void tma_store2d(const CUtensorMap* m, int c0, int c1, uint32_t src) {
  asm volatile("cp.async.bulk.tensor.2d.global.shared::cta.bulk_group [%0,{%2,%3}],[%1];" ::"l"(m), "r"(src), "r"(c0), "r"(c1) : "memory");
}
__device__ __forceinline__ void bulk_load(uint32_t dst, const void* src, uint32_t bytes, uint32_t bar) {
  asm volatile("cp.async.bulk.shared::cluster.global.mbarrier::complete_tx::bytes [%0],[%1],%2,[%3];" ::"r"(dst), "l"(src), "r"(bytes), "r"(bar) : "memory");
}
__device__ __forceinline__ void bulk_commit() { asm volatile("cp.async.bulk.commit_group;" ::: "memory"); }
__device__ __forceinline__ void bulk_wait() { asm volatile("cp.async.bulk.wait_group 0;" ::: "memory"); }
__device__ __forceinline__ void prefetch_map(const CUtensorMap* m) { asm volatile("prefetch.tensormap [%0];" ::"l"(m) : "memory"); }
__device__ __forceinline__ void stsm4(uint32_t a, uint32_t r0, uint32_t r1, uint32_t r2, uint32_t r3) {
  asm volatile("stmatrix.sync.aligned.m8n8.x4.shared.b16 [%0],{%1,%2,%3,%4};" ::"r"(a), "r"(r0), "r"(r1), "r"(r2), "r"(r3) : "memory");
}
__device__ __forceinline__ void stsm8f(uint32_t a, const float* v) { stsm4(a, pack(v[0], v[1]), pack(v[2], v[3]), pack(v[4], v[5]), pack(v[6], v[7])); }
__device__ __forceinline__ void stsm8s(uint32_t a, const float* v, float s0, float s1) {
  stsm4(a, pack(v[0] * s0, v[1] * s0), pack(v[2] * s1, v[3] * s1), pack(v[4] * s0, v[5] * s0), pack(v[6] * s1, v[7] * s1));
}
__device__ __forceinline__ void load_q(uint32_t (&q)[8], uint32_t a) {
  asm volatile("ldmatrix.sync.aligned.m8n8.x4.shared.b16 {%0,%1,%2,%3},[%4];" : "=r"(q[0]), "=r"(q[1]), "=r"(q[2]), "=r"(q[3]) : "r"(a) : "memory");
  asm volatile("ldmatrix.sync.aligned.m8n8.x4.shared.b16 {%0,%1,%2,%3},[%4];" : "=r"(q[4]), "=r"(q[5]), "=r"(q[6]), "=r"(q[7]) : "r"(a ^ 32) : "memory");
}
__device__ __forceinline__ void sts32(uint32_t a, uint32_t v) { asm volatile("st.shared.u32 [%0],%1;" ::"r"(a), "r"(v) : "memory"); }
__device__ __forceinline__ uint32_t lds32(uint32_t a) { uint32_t v; asm volatile("ld.shared.u32 %0,[%1];" : "=r"(v) : "r"(a) : "memory"); return v; }
__device__ __forceinline__ uint32_t lds_max4(uint32_t a) {
  uint4 v;
  asm volatile("ld.shared.v4.u32 {%0,%1,%2,%3},[%4];" : "=r"(v.x), "=r"(v.y), "=r"(v.z), "=r"(v.w) : "r"(a) : "memory");
  return max(max(v.x, v.y), max(v.z, v.w));
}
__device__ __forceinline__ float quad_sum(float v) { v += __shfl_xor_sync(~0u, v, 1); return v + __shfl_xor_sync(~0u, v, 2); }
__device__ __forceinline__ void cnt_add(uint32_t* c) { asm volatile("red.release.gpu.global.add.u32 [%0],1;" ::"l"(c) : "memory"); }
__device__ __forceinline__ uint32_t cnt_ld(uint32_t* c) {
  uint32_t v;
  asm volatile("ld.acquire.gpu.global.u32 %0,[%1];" : "=r"(v) : "l"(c) : "memory");
  return v;
}
__device__ __forceinline__ void cnt_wait(uint32_t* c, uint32_t target) {
  asm volatile(
      "{\n.reg .pred p;\n.reg .u32 n,v;\n"
      "mov.u32 n,0;\n"
      "CW_LOOP:\n"
      "ld.acquire.gpu.global.u32 v,[%0];\n"
      "setp.ge.u32 p,v,%1;\n"
      "@p bra CW_DONE;\n"
      "nanosleep.u32 40;\n"
      "add.u32 n,n,1;\n"
      "setp.lt.u32 p,n,4000000;\n"
      "@p bra CW_LOOP;\n"
      "trap;\n"
      "CW_DONE:\n}" ::"l"(c), "r"(target) : "memory");
}
__device__ __forceinline__ void sched_pin(float l0, float l1, uint32_t never) {
  asm volatile("{\n.reg .pred p;\nsetp.ne.u32 p,%3,0;\n@p st.shared.v2.f32 [%2],{%0,%1};\n}" ::"f"(l0), "f"(l1), "r"(SM_DUMMY), "r"(never) : "memory");
}

template <bool TR>
__device__ __forceinline__ void gemm_tile(float (&a0)[64], float (&a1)[64], uint32_t n0, uint32_t steps, bool leader) {
  mbar_wait(B_FULL + (n0 & 3) * 8, (n0 >> 2) & 1);
  {
    const uint32_t x = (SM_R >> 4) + (n0 & 3) * 2048, w = x + 1024;
    wg_fence();
    if (TR) wgmma_ss_n128_z<1, 0>(a0, desc(w), desc(x)); else wgmma_ss_n128_z<0, 1>(a0, desc(x), desc(w));
    if (TR) wgmma_ss_n128_z<1, 0>(a1, desc(w + 512), desc(x)); else wgmma_ss_n128_z<0, 1>(a1, desc(x + 512), desc(w));
    wg_commit();
  }
#pragma unroll 1
  for (uint32_t n = n0; n < n0 + steps; n++) {
    const uint32_t x = (SM_R >> 4) + (n & 3) * 2048, w = x + 1024, nn = min(n + 1, n0 + steps - 1);
#pragma unroll
    for (int kk = 0; kk < 4; kk++) {
      if (kk == 0 && n == n0) continue;
      if (kk < 2) wg_fence();
      if (TR) wgmma_ss_n128<1, 0>(a0, desc(w + kk * 128), desc(x + kk * 2), 1);
      else wgmma_ss_n128<0, 1>(a0, desc(x + kk * 2), desc(w + kk * 128), 1);
      if (!TR || kk == 1) { wg_commit(); wg_wait<1>(); }
      if (kk == 0) mbar_arrive_if(B_EMPTY + ((n - 1) & 3) * 8, leader);
      if (TR) wgmma_ss_n128<1, 0>(a1, desc(w + 512 + kk * 128), desc(x + kk * 2), 1);
      else wgmma_ss_n128<0, 1>(a1, desc(x + 512 + kk * 2), desc(w + kk * 128), 1);
      wg_commit();
      if (kk == 3) mbar_wait(B_FULL + (nn & 3) * 8, (nn >> 2) & 1);
      if (TR && kk > 0) wg_wait<0>(); else wg_wait<1>();
    }
  }
  wg_wait<0>();
  pin(a0); pin(a1);
}
__device__ __forceinline__ void q_block(const float* v, uint32_t qa, uint32_t& m) {
  uint32_t p[8], s0, s1;
#pragma unroll
  for (int e = 0; e < 8; e++) p[e] = pack(v[2 * e], v[2 * e + 1]);
  stsm4(qa, p[0], p[1], p[2], p[3]);
  stsm4(qa ^ 32, p[4], p[5], p[6], p[7]);
  asm("mul.rn.bf16x2 %0,%1,%1;" : "=r"(s0) : "r"(p[0]));
  asm("mul.rn.bf16x2 %0,%1,%1;" : "=r"(s1) : "r"(p[1]));
#pragma unroll
  for (int e = 2; e < 8; e += 2) {
    asm("fma.rn.bf16x2 %0,%1,%1,%0;" : "+r"(s0) : "r"(p[e]));
    asm("fma.rn.bf16x2 %0,%1,%1,%0;" : "+r"(s1) : "r"(p[e + 1]));
  }
  asm("max.NaN.bf16x2 %0,%0,%1;" : "+r"(m) : "r"(s0));
  asm("max.NaN.bf16x2 %0,%0,%1;" : "+r"(m) : "r"(s1));
}
__device__ __forceinline__ float q_bound(uint32_t m) { return quad_sum(__uint_as_float(m << 16) + __uint_as_float(m & 0xffff0000u)); }
__device__ __forceinline__ bool bound_exceeded(float qn2) { return !(qn2 * __uint_as_float(lds32(SM_KINFO)) <= 3500.f); }

__device__ __forceinline__ void lin_mma(float (&D)[20], uint32_t (&p)[8], uint32_t kv) {
  pin(p);
  wg_fence();
  wgmma_rs_n40_z<1>(D, p[0], p[1], p[2], p[3], desc(kv));
  wgmma_rs_n40<1>(D, p[4], p[5], p[6], p[7], desc(kv + 128), 1);
  wg_commit();
}
__device__ __forceinline__ void lin_out(float (&D)[20], uint32_t dst) {
  pin(D);
  const float i0 = rcp(D[16] + 1e-6f), i1 = rcp(D[18] + 1e-6f);
  stsm8s(dst, D, i0, i1);
  stsm8s(dst ^ 32, D + 8, i0, i1);
}
template <int M, int LO, int HI>
__device__ __forceinline__ void final_mma(float (&a)[64]) {
  wg_fence();
#pragma unroll
  for (int t = LO; t < HI; t++)
    wgmma_ss_n128<0, 1>(a, desc((SM_KV >> 4) + M * 2048 + (t >> 2) * 512 + (t & 3) * 2), desc((SM_R >> 4) + 2048 + (t >> 2) * 1024 + (t & 3) * 128), 1);
}
template <int M, int C0, int C1>
__device__ __forceinline__ void final_out(float (&a)[64], uint32_t sts, const CUtensorMap* m, int i, int j, bool issuer) {
  constexpr uint32_t base = SM_R + 3 * 32768 + M * 16384;
#pragma unroll
  for (int g = 4 * C0; g < 4 * C1 + 4; g++) stsm8f(base + (g >> 2) * 8192 + (sts ^ ((g & 3) << 5)), a + 8 * g);
  fence_async_smem();
  bar_sync<1, 128>();
  if (issuer && elect_one()) {
#pragma unroll
    for (int C = C0; C <= C1; C++) tma_store2d(m, 1024 + j * 128 + C * 64, i * 128 + M * 64, base + C * 8192);
    bulk_commit();
  }
}

__device__ __forceinline__ void attn_batch(float (&S)[32], uint32_t (&q)[8], float (&O)[16], uint32_t (&P)[16], uint32_t k16, int acc) {
  const uint32_t v16 = k16;
  wg_fence();
  wgmma_rs_n32<1>(O, P[0], P[1], P[2], P[3], desc(v16 + 4), acc);
  wgmma_rs_n64_z<0>(S, q[0], q[1], q[2], q[3], desc(k16));
  wgmma_rs_n32<1>(O, P[4], P[5], P[6], P[7], desc(v16 + 4 + 128), 1);
  wgmma_rs_n32<1>(O, P[8], P[9], P[10], P[11], desc(v16 + 4 + 256), 1);
  wgmma_rs_n64<0>(S, q[4], q[5], q[6], q[7], desc(k16 + 2), 1);
  wgmma_rs_n32<1>(O, P[12], P[13], P[14], P[15], desc(v16 + 4 + 384), 1);
  wg_commit();
}
template <int PIN>
__device__ __forceinline__ void attn_exp(float (&S)[32], uint32_t (&P)[16], float& l0, float& l1, uint32_t never, float (&Sn)[32], float (&O)[16]) {
#pragma unroll
  for (int i = 0; i < 16; i++) {
    if (i == 16 - PIN) sched_pin(l0, l1, never);
    const float a = ex2(S[2 * i]), b = ex2(S[2 * i + 1]);
    if (i & 1) { l1 += a; l1 += b; } else { l0 += a; l0 += b; }
    P[i] = pack(a, b);
  }
  pin(P);
  wg_wait<0>();
  pin(Sn); pin(O);
}

__device__ __forceinline__ void attn_finish(float (&O)[16], float l0, float l1, uint32_t oa, uint32_t bar) {
  const float r0 = rcp(quad_sum(l0)), r1 = rcp(quad_sum(l1));
  stsm8s(oa, O, r0, r1);
  stsm8s(oa ^ 32, O + 8, r0, r1);
  fence_async_smem();
  mbar_arrive(bar);
}
__device__ __forceinline__ void mma16816(float* d, const uint32_t* a, uint32_t b0, uint32_t b1) {
  asm("mma.sync.aligned.m16n8k16.row.col.f32.bf16.bf16.f32 {%0,%1,%2,%3},{%4,%5,%6,%7},{%8,%9},{%0,%1,%2,%3};"
      : "+f"(d[0]), "+f"(d[1]), "+f"(d[2]), "+f"(d[3]) : "r"(a[0]), "r"(a[1]), "r"(a[2]), "r"(a[3]), "r"(b0), "r"(b1));
}
__device__ __noinline__ void attn_general(uint32_t pass, uint32_t qtop, uint32_t a) {
  const uint32_t lane = threadIdx.x & 31;
#pragma unroll 1
  for (; pass < 4; pass++) {
    float m0 = -INFINITY, m1 = -INFINITY, l0 = 0.f, l1 = 0.f, O[16];
    uint32_t q[8];
    load_q(q, qtop - pass * 8192);
#pragma unroll
    for (int e = 0; e < 16; e++) O[e] = 0.f;
#pragma unroll 1
    for (uint32_t b = 0; b < 64; b++) {
      const uint32_t s = (b >> 2) & 3, kb = SM_KV + (b & 15) * 4096, vb = SM_KV + ((b + 4) & 15) * 4096;
      if ((b & 3) == 0) stage_landed(8 + 4 * a + ((s + 1) & 3));
      float S[16];
      uint32_t P[8];
#pragma unroll
      for (int n = 0; n < 4; n++) {
        uint32_t k[4];
        asm volatile("ldmatrix.sync.aligned.m8n8.x4.shared.b16 {%0,%1,%2,%3},[%4];" : "=r"(k[0]), "=r"(k[1]), "=r"(k[2]), "=r"(k[3])
                     : "r"(kb + n * 1024 + (lane & 7) * 128 + (((lane >> 3) ^ (lane & 7)) << 4)) : "memory");
        S[4 * n] = S[4 * n + 1] = S[4 * n + 2] = S[4 * n + 3] = 0.f;
        mma16816(S + 4 * n, q, k[0], k[1]);
        mma16816(S + 4 * n, q + 4, k[2], k[3]);
      }
      float x0 = m0, x1 = m1;
#pragma unroll
      for (int e = 0; e < 4; e++) {
        x0 = fmaxf(x0, fmaxf(S[4 * e], S[4 * e + 1]));
        x1 = fmaxf(x1, fmaxf(S[4 * e + 2], S[4 * e + 3]));
      }
      x0 = fmaxf(x0, __shfl_xor_sync(~0u, x0, 1)); x1 = fmaxf(x1, __shfl_xor_sync(~0u, x1, 1));
      x0 = fmaxf(x0, __shfl_xor_sync(~0u, x0, 2)); x1 = fmaxf(x1, __shfl_xor_sync(~0u, x1, 2));
      const float y0 = x0 == -INFINITY ? 0.f : x0, y1 = x1 == -INFINITY ? 0.f : x1;
      const float al0 = ex2(m0 - y0), al1 = ex2(m1 - y1);
      m0 = x0; m1 = x1;
      l0 *= al0; l1 *= al1;
#pragma unroll
      for (int e = 0; e < 4; e++) {
        const float pa = ex2(S[4 * e] - y0), pb = ex2(S[4 * e + 1] - y0), pc = ex2(S[4 * e + 2] - y1), pd = ex2(S[4 * e + 3] - y1);
        l0 += pa + pb; l1 += pc + pd;
        P[2 * e] = pack(pa, pb); P[2 * e + 1] = pack(pc, pd);
        O[4 * e] *= al0; O[4 * e + 1] *= al0; O[4 * e + 2] *= al1; O[4 * e + 3] *= al1;
      }
#pragma unroll
      for (int n = 0; n < 4; n++) {
        uint32_t v[4];
        asm volatile("ldmatrix.sync.aligned.m8n8.x4.trans.shared.b16 {%0,%1,%2,%3},[%4];" : "=r"(v[0]), "=r"(v[1]), "=r"(v[2]), "=r"(v[3])
                     : "r"(vb + lane * 128 + (((4 + n) ^ (lane & 7)) << 4)) : "memory");
        mma16816(O + 4 * n, P, v[0], v[1]);
        mma16816(O + 4 * n, P + 4, v[2], v[3]);
      }
      if ((b & 3) == 3) {
        asm volatile("bar.sync %0,128;" ::"r"(4 + a) : "memory");
        mbar_arrive_if(B_KVEMPTY + s * 8, (threadIdx.x & 127) == 0);
      }
    }
    attn_finish(O, l0, l1, qtop - pass * 8192, (pass == 3 ? B_OLAST : B_OSTORE) + a * 8);
  }
}

__device__ __noinline__ void kv_reduce(Small* gs, int hp, int i) {
  const int lane = threadIdx.x & 31;
  if (lane == 0) cnt_add(gs->flags + c_part(hp >> 1, hp & 1));
  __syncwarp();
  cnt_wait(gs->flags + c_part(hp >> 1, hp & 1), 16);
  const float* zp = gs->zpart + (hp * 16 + (lane >> 2)) * 64 + 4 * i + (lane & 3);
  float z = __ldcg(zp) + __ldcg(zp + 8 * 64);
  const float4* pp = gs->part + hp * 16 * 512 + i * 32 + lane;
  float4 acc = make_float4(0.f, 0.f, 0.f, 0.f);
#pragma unroll 1
  for (int r = 0; r < 16; r += 4) {
    const float4 v0 = __ldcg(pp + (r + 0) * 512), v1 = __ldcg(pp + (r + 1) * 512), v2 = __ldcg(pp + (r + 2) * 512), v3 = __ldcg(pp + (r + 3) * 512);
    acc.x += (v0.x + v1.x) + (v2.x + v3.x); acc.y += (v0.y + v1.y) + (v2.y + v3.y);
    acc.z += (v0.z + v1.z) + (v2.z + v3.z); acc.w += (v0.w + v1.w) + (v2.w + v3.w);
  }
  z += __shfl_xor_sync(~0u, z, 4); z += __shfl_xor_sync(~0u, z, 8); z += __shfl_xor_sync(~0u, z, 16);
  uint32_t* blob = gs->blob + hp * 2048;
  const int q = i >> 2, d0 = (i & 3) * 16 + (lane >> 2);
  uint32_t* bp = blob + d0 * 32 + ((q ^ (d0 & 7)) << 2) + (lane & 3);
  bp[0] = pack(acc.x, acc.y);
  bp[8 * 32] = pack(acc.z, acc.w);
  const int d = 4 * i + (lane & 3);
  if (lane < 16) blob[d * 32 + ((4 ^ (d & 7)) << 2) + (lane >> 2)] = pack(z, z);
  fence_async_gmem();
  __syncwarp();
  if (lane == 0) cnt_add(gs->flags + c_red(hp >> 1));
}

__device__ __noinline__ void store_passes(Small* gs, const CUtensorMap* m, int i, int j) {
  const bool sender = elect_one();
#pragma unroll 1
  for (int u = 0; u < 6; u++) {
    const int p = u >> 1, a = u & 1;
    mbar_wait_wd(B_OSTORE + a * 8, p & 1);
    if (sender) {
      tma_store2d(m, (p < 2 ? a : 2) * 256 + j * 32, i * 128 + (p < 2 ? (j >> 2) ^ p : a) * 64, SM_Q + (6 - 2 * p + a) * 4096);
      bulk_commit();
      bulk_wait();
      if (a && p) cnt_add(gs->flags + c_row(i, p + 1));
      if (u == 5) mbar_arrive(B_QFREE);
    }
  }
}
__device__ __forceinline__ void leave(Small* gs) {
  const int lane = threadIdx.x & 31;
  uint32_t last = 0;
  if (lane == 0) asm volatile("atom.relaxed.gpu.global.add.u32 %0,[%1],1;" : "=r"(last) : "l"(gs->flags + F_DONE) : "memory");
  if (__shfl_sync(~0u, last, 0) == gridDim.x - 1) {
    fence_acquire();
    uint4* fl = (uint4*)gs->flags;
    fl[lane] = make_uint4(0, 0, 0, 0);
    if (lane < 25) { fl[32 + lane * 8] = make_uint4(0, 0, 0, 0); fl[33 + lane * 8] = make_uint4(0, 0, 0, 0); }
  }
}

__global__ void __launch_bounds__(512, 1) fused_kernel(int never, Small* __restrict__ gs, const __grid_constant__ Maps mp) {
  extern __shared__ __align__(1024) char smem_raw[];
  const int warp = __shfl_sync(~0u, (int)(((0x1320 >> ((threadIdx.x >> 7) * 4)) & 3) * 4 + ((threadIdx.x >> 5) & 3)), 0);
  const int lane = threadIdx.x & 31;
  const int j = (blockIdx.x & 3) + ((blockIdx.x >> 6) << 2), i = (blockIdx.x >> 2) & 15;
  const uint32_t hf = j >> 2;

  if (warp == 0) {
    if (elect_one()) {
#pragma unroll
      for (int s = 0; s < 10; s++) mbar_init(SM_BAR + s * 8, 1);
      asm volatile("fence.mbarrier_init.release.cluster;" ::: "memory");
      fence_async_smem();
    }
#pragma unroll 1
    for (uint32_t st = 0; st < 8; st++)
      if (elect_one()) {
        mbar_expect(B_HX + st * 8, 16384);
        tma3d(SB + st * 16384, &mp.xBh, 0, i * 128 + hf * 64, st * 2, B_HX + st * 8);
        if (st == 0) {
          mbar_expect(B_HK, 65536);
          tma2d(SM_KV, &mp.wkv[(j >> 1) & 1], 0, 0, B_HK);
          tma2d(SM_KV + 32768, &mp.wkv[(j >> 1) & 1], 0, 256, B_HK);
        }
        if (st == 1) {
          mbar_expect(B_HW, 16384);
          tma2d(SM_Q, &mp.wqh, j * 128, 0, B_HW);
        }
        if (st == 7 && i >= 3 && i < 8)
          asm volatile("cp.async.bulk.prefetch.tensor.2d.L2.global [%0,{%1,%2}];" ::"l"(&mp.wqh), "r"(j * 128), "r"(i * 128) : "memory");
      }
  } else if (warp < 3) {
    if (elect_one()) {
      if (warp == 1) {
#pragma unroll 1
        for (int s = 10; s < 39; s++) mbar_init(SM_BAR + s * 8, 1);
      } else {
#pragma unroll 1
        for (int s = 39; s < 55; s++) mbar_init(SM_BAR + s * 8, s < 44 ? 2 : s == 44 ? 15 : 128);
        sts32(SM_UNSAFE, 0);
      }
      asm volatile("fence.mbarrier_init.release.cluster;" ::: "memory");
      fence_async_smem();
    }
  }
  __syncthreads();

  if (warp < 4) {
    asm volatile("setmaxnreg.dec.sync.aligned.u32 32;");
    if (warp == 0) {
#pragma unroll 1
      for (int w = 1; w < 8; w++) {
        mbar_wait(B_HT - min(max(w - 2, 0), 4) * 8, 0);
        if (elect_one()) {
          mbar_expect(B_HW + w * 8, 16384);
          tma2d(head_wq(w), &mp.wqh, j * 128, w * 128, B_HW + w * 8);
          if (w == 3 && i >= 8)
            asm volatile("cp.async.bulk.prefetch.tensor.2d.L2.global [%0,{%1,%2}];" ::"l"(&mp.wqh), "r"(j * 128 + 64), "r"(i * 128 - 1024) : "memory");
        }
      }
      mbar_wait(B_HD0, 0);
      mbar_wait(B_KINFO, 0);
#pragma unroll 1
      for (uint32_t n = 0; n < 64; n++) {
        const uint32_t t = n >> 4, s = n & 3, f = B_FULL + s * 8, k = (n & 15) * 64;
        const bool kvt = t == 1 || t == 2;
        mbar_wait(B_EMPTY + s * 8, ((n >> 2) & 1) ^ 1);
        if (elect_one()) {
          mbar_expect(f, 32768);
          tma2d(SM_R + s * 32768, &mp.x[t > 0], k, i * 128, f);
          tma3d(SM_R + s * 32768 + 16384, &mp.w[(t + 1) >> 1], kvt ? (2 * j + t - 1) * 64 : 0, k, kvt ? 1 : 2 * j, f);
        }
      }
      mbar_wait(B_EMPTY, 1);
      cnt_wait(gs->flags + c_red(j), 32);
      fence_async_gmem();
      if (elect_one()) {
        mbar_expect(B_FULL, 16384);
        bulk_load(SM_R, gs->blob + j * 4096, 16384, B_FULL);
      }
      uint32_t nx = 0, ready = 0;
#pragma unroll 1
      for (uint32_t m = 0; m < 30; m++) {
        const uint32_t s = (m + 1) & 3, f = B_FULL + s * 8, kb = m < 16 ? (m & 7) * 2 + (m >> 3) : m - 16;
        mbar_wait(B_EMPTY + s * 8, (((m + 1) >> 2) & 1) ^ 1);
        if (elect_one()) {
          mbar_expect(f, 32768);
          tma5d(SM_R + s * 32768 + 16384, &mp.wo[m >> 4], kb >> 2, m < 28 ? (kb & 3) * 2 : (m & 3) * 4 + 2, 2 * j, f);
          if (m >= 28) tma5d(SM_R + s * 32768, &mp.wo[1], 3, (m & 3) * 4, 2 * j, f);
        }
        if (ready <= m) {
          if (m & 1) cnt_wait(gs->flags + c_row(i, m >> 3), 8);
          if (__shfl_sync(~0u, cnt_ld(gs->flags + c_row(i, m >> 3)), 0) >= 8) ready += 8;
          fence_async_gmem();
        }
#pragma unroll 1
        for (; nx <= m && nx < ready && nx < 28; nx++)
          if (elect_one())
            tma2d(SM_R + ((nx + 1) & 3) * 32768, &mp.oL[nx >> 4], (nx < 16 ? (nx & 7) * 2 + (nx >> 3) : nx - 16) * 64, i * 128, B_FULL + ((nx + 1) & 3) * 8);
      }
      mbar_wait(B_FX, 0);
      mbar_wait(B_FX + 8, 0);
      leave(gs);
    } else if (warp == 3) {
      if ((uint32_t)__cvta_generic_to_shared(smem_raw) != SB) __trap();
#pragma unroll 1
      for (int k = 0; k < 15; k++) if (elect_one()) prefetch_map(&mp.kvS + k);
#pragma unroll 1
      for (int t = 0; t < 2; t++) {
        mbar_wait(B_GPART, t);
        kv_reduce(gs, 2 * j + t, i);
      }
      const bool sender = elect_one();
#pragma unroll 1
      for (int r = 0; r < 8; r++) {
        if (r <= 4) mbar_wait(B_GSTORE + (r & 3) * 8, r >> 2); else __nanosleep(400);
        if (sender) {
          tma_store2d(&mp.st[r >> 2], j * 128 + (r & 2) * 32, i * 128 + (r & 1) * 64, r < 4 ? SM_R + 3 * 32768 + r * 8192 : r == 4 ? SM_R : SM_Q + (r - 4) * 8192);
          bulk_commit();
          bulk_wait();
          if (r == 3 || r == 4) mbar_arrive(B_EMPTY + (r & 3) * 8);
          if ((r & 5) == 1) cnt_add(gs->flags + c_row(i, r >> 1));
        }
      }
    } else {
      if (warp == 1) {
        uint4 a;
        uint32_t spins = 0, g = 0, rel = 1;
        mbar_wait(B_HD1, 0);
        while (true) {
          asm volatile("ld.acquire.gpu.global.v4.u32 {%0,%1,%2,%3},[%4];" : "=r"(a.x), "=r"(a.y), "=r"(a.z), "=r"(a.w) : "l"(gs->flags + F_KVB + lane * 4) : "memory");
          const uint32_t rdy = __ballot_sync(~0u, (a.x & a.y & a.z & a.w & 1u) != 0);
          fence_async_gmem();
          if (g == 0 && (rdy & 3u) == 3u) {
            g = 1;
            if (elect_one()) {
              mbar_expect(B_KVFULL, 16384);
              tma2d(SM_KV, &mp.kvb, 0, 0, B_KVFULL);
            }
          }
          if (rdy == ~0u) break;
          __nanosleep(100);
          if (++spins > 4000000u) __trap();
        }
        const uint32_t knm = __reduce_max_sync(~0u, __float_as_uint(__uint_as_float(a.x) + __uint_as_float(a.y)));
        const uint32_t vnm = __reduce_max_sync(~0u, max(a.z, a.w));
        if (elect_one()) {
          sts32(SM_KINFO, vnm - 0x17800000u <= 0x50000000u ? knm : 0x7f800000u);
          mbar_arrive(B_KINFO);
        }
        mbar_wait(B_HD0, 0);
#pragma unroll 1
        for (g = 1; g <= 64; g++) {
          const uint32_t s = g & 3;
          mbar_wait(B_KVEMPTY + s * 8, ((g >> 2) & 1) ^ 1);
          if (elect_one()) {
            mbar_expect(B_KVFULL + s * 8, 16384);
            tma2d(SM_KV + s * 16384, &mp.kvb, 0, (g & 15) * 128, B_KVFULL + s * 8);
          }
#pragma unroll 1
          for (; rel <= g && g >= 3; rel++) {
            mbar_wait(B_KVFULL + (rel & 3) * 8, (rel >> 2) & 1);
            if (rel == 16) mbar_wait(B_QRDY, 0);
            asm volatile("bar.arrive %0,160;" ::"r"(8 + (rel & 3)) : "memory");
            asm volatile("bar.arrive %0,160;" ::"r"(12 + (rel & 3)) : "memory");
          }
        }
      } else {
        store_passes(gs, &mp.obS, i, j);
      }
      const int M = warp & 1;
      mbar_wait_wd(B_OLAST + M * 8, 0);
      if (elect_one()) {
        tma_store2d(&mp.obS, 768 + j * 32, i * 128 + M * 64, SM_Q + M * 4096);
        bulk_commit();
        bulk_wait();
        cnt_add(gs->flags + c_row(i, 4 + M));
      }
      __syncwarp();
      mbar_wait_wd(M ? B_KVEMPTY + 24 : B_OLAST + 8, M);
      cnt_wait(gs->flags + c_row(i, 4 + M), 8);
      fence_async_gmem();
      if (elect_one()) {
        mbar_expect(B_FX + M * 8, 32768);
        tma3d(SM_KV + M * 32768, &mp.obH, 0, i * 128 + M * 64, 12, B_FX + M * 8);
      }
    }
    if (warp == 2) {
      mbar_wait_wd(B_END, 0);
    } else {
      mbar_arrive_if(B_END, lane == 0);
    }
  } else if (warp < 8) {
    asm volatile("setmaxnreg.inc.sync.aligned.u32 176;");
    const uint32_t tid = threadIdx.x & 127;
    const bool leader = tid == 0;
    const uint32_t row = (tid >> 5) * 16 + (tid & 15);
    const uint32_t sts = row * 128 + ((((tid >> 4) & 1) ^ (tid & 7)) << 4);
    float a0[64], a1[64];
    {
      float a2[32];
      fresh(a0); fresh(a2);
      mbar_wait(B_FULL, 0);
#pragma unroll 1
      for (uint32_t n = 0; n < 16; n++) {
        const uint32_t x = (SM_R >> 4) + (n & 3) * 2048, w = x + 1024, nn = min(n + 1, 15u);
        wg_fence();
#pragma unroll
        for (int kk = 0; kk < 4; kk++) {
          wgmma_ss_n128<0, 1>(a0, desc(x + 512 - hf * 512 + kk * 2), desc(w + kk * 128), kk > 0 || n > 0);
          wg_commit();
          wg_wait<1>();
          wgmma_ss_n64<0, 1>(a2, desc(x + hf * 512 + kk * 2), desc(w + 512 + kk * 128), kk > 0 || n > 0);
          wg_commit();
          if (kk == 3) mbar_wait(B_FULL + (nn & 3) * 8, (nn >> 2) & 1);
          wg_wait<1>();
          if (kk == 0) mbar_arrive_if(B_EMPTY + ((n - 1) & 3) * 8, leader && n > 0);
        }
      }
      wg_wait<0>();
      mbar_arrive_if(B_EMPTY + 3 * 8, leader);
      pin(a0); pin(a2);
      const uint32_t qa = SM_Q + row * 64 + ((((tid >> 4) & 1) ^ ((tid >> 1) & 3)) << 4), qb = qa - hf * 4096, qc = qa + hf * 4096;
      uint32_t m = 0;
      q_block(a0, qa + 4 * 4096, m);
      q_block(a0 + 16, qa + 5 * 4096, m);
      q_block(a0 + 32, qb + 3 * 4096, m);
      q_block(a0 + 48, qb + 4096, m);
      q_block(a2, qc + 2 * 4096, m);
      q_block(a2 + 16, qc, m);
      if (bound_exceeded(q_bound(m))) sts32(SM_UNSAFE, 1);
      mbar_arrive(B_QRDY);
    }
#pragma unroll 1
    for (int t = 0; t < 2; t++) {
      gemm_tile<true>(a0, a1, 16 + t * 16, 16, leader);
      constexpr uint32_t xs = SM_R + 3 * 32768;
      bar_sync<1, 128>();
#pragma unroll
      for (int g = 0; g < 8; g++) stsm8f(xs + (g >> 2) * 9216 + (sts ^ ((g & 3) << 5)), a1 + 8 * g);
      asm volatile("st.shared.v4.u32 [%0],{%1,%1,%1,%1};" ::"r"(xs + 8192 + (tid >> 6) * 8192 + tid * 16), "r"(0x3f803f80u) : "memory");
      fence_async_smem();
      uint32_t p[32];
#pragma unroll
      for (int g = 0; g < 24; g++) p[g] = phi2(a0[2 * g], a0[2 * g + 1]);
#pragma unroll
      for (int g = 0; g < 24; g++) asm volatile("" : "+r"(p[g])::"memory");
      bar_sync<1, 128>();
      float D[36];
      wg_fence();
      wgmma_rs_n72_z<0>(D, p[0], p[1], p[2], p[3], desc(xs >> 4));
#pragma unroll
      for (int kk = 1; kk < 6; kk++)
        wgmma_rs_n72<0>(D, p[4 * kk], p[4 * kk + 1], p[4 * kk + 2], p[4 * kk + 3], desc((xs >> 4) + (kk >> 2) * 576 + (kk & 3) * 2), 1);
      wg_commit();
#pragma unroll
      for (int g = 24; g < 32; g++) p[g] = phi2(a0[2 * g], a0[2 * g + 1]);
#pragma unroll
      for (int g = 24; g < 32; g++) asm volatile("" : "+r"(p[g])::"memory");
      wg_fence();
#pragma unroll
      for (int kk = 6; kk < 8; kk++)
        wgmma_rs_n72<0>(D, p[4 * kk], p[4 * kk + 1], p[4 * kk + 2], p[4 * kk + 3], desc((xs >> 4) + (kk >> 2) * 576 + (kk & 3) * 2), 1);
      wg_commit();
      const int slot = (2 * j + t) * 16 + i;
      float* zp = gs->zpart + slot * 64 + (tid >> 5) * 16 + ((tid & 31) >> 2);
      float4* pp = gs->part + slot * 512 + tid;
      wg_wait<0>();
      pin(D);
      mbar_arrive_if(B_EMPTY + 3 * 8, leader);
      if ((tid & 3) == 0) { zp[0] = D[32]; zp[8] = D[34]; }
#pragma unroll
      for (int q = 0; q < 4; q++) {
        if (tid < 64) pp[q * 128] = make_float4(D[4 * q], D[4 * q + 1], D[4 * q + 2], D[4 * q + 3]);
        else pp[q * 128] = make_float4(D[16 + 4 * q], D[17 + 4 * q], D[18 + 4 * q], D[19 + 4 * q]);
      }
      mbar_arrive(B_GPART);
    }
#pragma unroll 1
    for (int t = 0;; t++) {
      gemm_tile<false>(a0, a1, t == 0 ? 48 : 49 + t * 16, t == 2 ? 12 : 16, leader);
      if (t == 2) break;
      bar_sync<1, 128>();
      if (t == 1) mbar_wait(B_QFREE, 0);
      const uint32_t stg = (t == 0 ? SM_R + 3 * 32768 : SM_Q) + sts, stg0 = t == 0 ? stg : SM_R + sts;
#pragma unroll
      for (int g = 0; g < 8; g++) stsm8f(((g < 4 ? stg0 : stg) ^ ((g & 3) << 5)) + (g >> 2) * 16384, a0 + 8 * g);
#pragma unroll
      for (int g = 0; g < 8; g++) stsm8f((stg ^ ((g & 3) << 5)) + 8192 + (g >> 2) * 16384, a1 + 8 * g);
      if (t == 0) {
        mbar_wait(B_FULL, 0);
        __syncwarp();
#pragma unroll 1
        for (int r = 0; r < 4; r++) {
          uint32_t p0[8], p1[8];
          float D0[20], D1[20];
          const uint32_t dst = stg + r * 8192, kv = (SM_R >> 4) + (r >> 1) * 512;
          load_q(p0, dst);
          load_q(p1, dst ^ 64);
#pragma unroll
          for (int g = 0; g < 8; g++) p0[g] = phi2p(p0[g]);
          lin_mma(D0, p0, kv);
#pragma unroll
          for (int g = 0; g < 8; g++) p1[g] = phi2p(p1[g]);
          lin_mma(D1, p1, kv + 256);
          wg_wait<1>();
          lin_out(D0, dst);
          wg_wait<0>();
          lin_out(D1, dst ^ 64);
          fence_async_smem();
          mbar_arrive(B_GSTORE + r * 8);
        }
        mbar_arrive_if(B_EMPTY, leader);
      } else {
        fence_async_smem();
        mbar_arrive(B_GSTORE);
      }
    }
    mbar_wait(B_FULL + 8, 1);
    mbar_wait(B_FULL + 16, 1);
    mbar_wait(B_FX + 8, 0);
    final_mma<1, 0, 16>(a1);
    wg_commit();
    mbar_wait(B_FX, 0);
    final_mma<0, 0, 6>(a0);
    wg_commit();
    wg_wait<1>();
    pin(a1);
    final_out<1, 0, 1>(a1, sts, &mp.st[1], i, j, warp == 4);
    final_mma<0, 6, 16>(a0);
    wg_commit();
    wg_wait<0>();
    pin(a0);
    final_out<0, 0, 0>(a0, sts, &mp.st[1], i, j, warp == 4);
    final_out<0, 1, 1>(a0, sts, &mp.st[1], i, j, warp == 4);
    bulk_wait();
    mbar_arrive_if(B_END, lane == 0);
  } else {
    asm volatile("setmaxnreg.inc.sync.aligned.u32 152;");
    const uint32_t a = (warp >> 2) - 2;
    const uint32_t tid = threadIdx.x & 127;
    const bool leader = tid == 0;
    const uint32_t row = (tid >> 5) * 16 + (tid & 15);
    const uint32_t qoff = row * 64 + ((((tid >> 4) & 1) ^ ((tid >> 1) & 3)) << 4);
    if (a == 0) {
      float acc[32];
      fresh(acc);
#pragma unroll 1
      for (uint32_t st = 0; st < 8; st++) {
        const uint32_t x = (SB >> 4) + st * 1024, w = head_wq(st) >> 4;
        mbar_wait(st == 0 ? B_HX : B_KVSENT, 0);
        mbar_wait(B_HW + st * 8, 0);
        wg_fence();
#pragma unroll
        for (int kk = 0; kk < 8; kk++) wgmma_ss_n64<0, 1>(acc, desc(x + (kk >> 2) * 512 + (kk & 3) * 2), desc(w + kk * 128), kk > 0 || st > 0);
        wg_commit();
        if (st < 2) {
          wg_wait<0>();
          mbar_arrive_if(B_HT - st * 32, leader);
        }
      }
      wg_wait<0>();
      pin(acc);
      mbar_arrive_if(B_HD0, leader);
      uint32_t m = 0;
      q_block(acc, SM_Q + 6 * 4096 + qoff, m);
      q_block(acc + 16, SM_Q + 7 * 4096 + qoff, m);
      m = __reduce_max_sync(~0u, __float_as_uint(q_bound(m)));
      sts32(SM_WMAX + 16 + (tid >> 5) * 4, m);
    } else {
      float acc[8];
      uint32_t* flagp = gs->flags + F_KVB + (i * 2 + hf) * 4 + (j & 3);
      fresh(acc);
      mbar_wait(B_HK, 0);
      {
        const uint32_t ad = SM_KV + (tid >> 3) * 1024 + 512 + ((tid >> 1) & 3) * 128 + ((((j & 1) * 2 + (tid & 1)) ^ ((tid >> 1) & 3)) << 4) + (tid & 2) * 32;
        uint4 u[8];
#pragma unroll
        for (int e = 0; e < 8; e++)
          asm volatile("ld.shared.v4.u32 {%0,%1,%2,%3},[%4];" : "=r"(u[e].x), "=r"(u[e].y), "=r"(u[e].z), "=r"(u[e].w) : "r"((ad ^ ((e & 1) * 64)) + (e >> 1) * 16384) : "memory");
#pragma unroll
        for (int e = 0; e < 8; e++)
          asm volatile("st.shared.v4.u32 [%4],{%0,%1,%2,%3};" ::"r"(u[e].x), "r"(u[e].y), "r"(u[e].z), "r"(u[e].w), "r"((ad ^ (64 - (e & 1) * 64)) + (e >> 1) * 16384) : "memory");
      }
      fence_async_smem();
      bar_sync<3, 128>();
#pragma unroll 1
      for (uint32_t st = 0; st < 8; st++) {
        const uint32_t x = (SB >> 4) + st * 1024, w = (SM_KV >> 4) + st * 512 + (j & 1) * 2;
        mbar_wait(B_HX + st * 8, 0);
        wg_fence();
#pragma unroll
        for (int kk = 0; kk < 8; kk++)
          wgmma_ss_n16<0, 1>(acc, desc(x + (kk >> 2) * 512 + (kk & 3) * 2), mkdesc(w + kk * 64, 16, 512, 2), kk > 0 || st > 0);
        wg_commit();
        wg_wait<1>();
        mbar_arrive_if(B_HT - (st / 3) * 8, leader && ((0x52u >> st) & 1));
      }
      wg_wait<0>();
      pin(acc);
      mbar_arrive_if(B_HD1, leader);
      const float c = (j & 2) ? 1.f : 0.17677669529663687f * 1.4426950408889634f;
#pragma unroll
      for (int e = 0; e < 8; e++) acc[e] *= c;
      constexpr uint32_t stg = SM_Q + 4 * 4096;
      stsm8f(stg + row * 32 + (tid & 16), acc);
      fence_async_smem();
      bar_sync<3, 128>();
      const bool sender = elect_one() && warp == 12;
      if (sender) {
        tma_store2d(&mp.kvS, (j & 3) * 16, (i * 128 + hf * 64 + (j & 2) * 64) & 2047, stg);
        bulk_commit();
      }
      const float n0 = quad_sum(acc[0] * acc[0] + acc[1] * acc[1] + acc[4] * acc[4] + acc[5] * acc[5]);
      const float n1 = quad_sum(acc[2] * acc[2] + acc[3] * acc[3] + acc[6] * acc[6] + acc[7] * acc[7]);
      sts32(SM_WMAX + (tid >> 5) * 4, __reduce_max_sync(~0u, max(__float_as_uint(n0), __float_as_uint(n1))));
      bar_sync<3, 128>();
      if (sender) {
        const uint32_t m = lds_max4(SM_WMAX) | 1u;
        bulk_wait();
        mbar_arrive(B_KVSENT);
        asm volatile("st.release.gpu.global.u32 [%0],%1;" ::"l"(flagp), "r"(m) : "memory");
      }
      __syncwarp();
    }
    bar_sync<2, 256>();
    const uint32_t qm = lds_max4(SM_WMAX + 16);
    const uint32_t qtop = SM_Q + (6 + a) * 4096 + qoff, kv16 = SM_KV >> 4, obar = B_OSTORE + a * 8;
    float O[16], S0[32], l0 = 0.f, l1 = 0.f;
    uint32_t q[8];
    load_q(q, qtop);
    mbar_wait(B_KVFULL, 0);
    wg_fence();
    wgmma_rs_n64_z<0>(S0, q[0], q[1], q[2], q[3], desc(kv16));
    wgmma_rs_n64<0>(S0, q[4], q[5], q[6], q[7], desc(kv16 + 2), 1);
    wg_commit();
    wg_wait<0>();
    pin(S0);
    mbar_wait(B_KINFO, 0);
    uint32_t pass = 0;
    if (__shfl_sync(~0u, (uint32_t)bound_exceeded(__uint_as_float(qm)), 0) == 0) {
      float S1[32];
      uint32_t P0[16], P1[16];
#pragma unroll
      for (int e = 0; e < 16; e++) { O[e] = 0.f; P1[e] = 0; }
      pin(O); pin(P1);
      uint32_t b = 0;
      const uint32_t nb = 8 + 4 * a;
#define ATTN_STAGE(u)                                                                            \
  attn_batch(S1, q, O, P1, kv16 + u * 1024 + 512, 1);                                            \
  stage_landed(nb + ((u + 1) & 3));                                                              \
  attn_exp<3>(S0, P0, l0, l1, never, S1, O);                                                  \
  mbar_arrive_if(B_KVEMPTY + u * 8, leader);                                                     \
  if (u == 3) load_q(q, qtop - min((b + 1) >> 2, 3u) * 8192);                                    \
  attn_batch(S0, q, O, P0, kv16 + ((u + 1) & 3) * 1024, u > 0 || b > 0);                         \
  attn_exp<1>(S1, P1, l0, l1, never, S0, O);
#pragma unroll 1
      while (true) {
        ATTN_STAGE(0)
#pragma unroll 1
        while (true) {
          ATTN_STAGE(1)
          ATTN_STAGE(2)
          ATTN_STAGE(3)
          b++;
          if (b & 3) break;
          if (b == 16 || (b == 4 && __shfl_sync(~0u, lds32(SM_UNSAFE), 0))) goto fast_done;
          float r0 = l0, r1 = l1;
          l0 = 0.f; l1 = 0.f;
          attn_batch(S1, q, O, P1, kv16 + 512, 1);
          stage_landed(nb + 1);
          r0 = rcp(quad_sum(r0)); r1 = rcp(quad_sum(r1));
          attn_exp<3>(S0, P0, l0, l1, never, S1, O);
          mbar_arrive_if(B_KVEMPTY, leader);
          const uint32_t oa = qtop + 8192 - b * 2048;
          stsm8s(oa, O, r0, r1);
          stsm8s(oa ^ 32, O + 8, r0, r1);
          attn_batch(S0, q, O, P0, kv16 + 1024, 0);
          fence_async_smem();
          mbar_arrive(obar);
          attn_exp<1>(S1, P1, l0, l1, never, S0, O);
        }
      }
    fast_done:
      wg_fence();
#pragma unroll
      for (int kk = 0; kk < 4; kk++)
        wgmma_rs_n32<1>(O, P1[4 * kk], P1[4 * kk + 1], P1[4 * kk + 2], P1[4 * kk + 3], desc(kv16 + 512 + 4 + kk * 128), 1);
      wg_commit();
      wg_wait<0>();
      pin(O);
      pass = b >> 2;
      attn_finish(O, l0, l1, qtop + 8192 - pass * 8192, pass == 4 ? obar + 16 : obar);
    }
    if (pass < 4) attn_general(pass, qtop, a);
    mbar_arrive_if(B_END, lane == 0);
  }
}

typedef CUresult (*EncodeFn)(CUtensorMap*, CUtensorMapDataType, cuuint32_t, void*, const cuuint64_t*, const cuuint64_t*, const cuuint32_t*,
                             const cuuint32_t*, CUtensorMapInterleave, CUtensorMapSwizzle, CUtensorMapL2promotion, CUtensorMapFloatOOBfill);

struct Dim { uint64_t size, stride; uint32_t box; };
template <int N>
void mapnd(EncodeFn enc, CUtensorMap* m, const void* p, const Dim (&d)[N], CUtensorMapSwizzle sw = CU_TENSOR_MAP_SWIZZLE_128B) {
  cuuint64_t gd[N], gs[N];
  cuuint32_t bd[N], es[N];
  for (int k = 0; k < N; k++) { gd[k] = d[k].size; gs[k] = d[k].stride * 2; bd[k] = d[k].box; es[k] = 1; }
  enc(m, CU_TENSOR_MAP_DATA_TYPE_BFLOAT16, N, (void*)p, gd, gs + 1, bd, es, CU_TENSOR_MAP_INTERLEAVE_NONE, sw,
      CU_TENSOR_MAP_L2_PROMOTION_L2_128B, CU_TENSOR_MAP_FLOAT_OOB_FILL_NONE);
}

}

extern "C" void kernel_launch(void* const* d_in, const int* in_sizes, int n_in, void* d_out, int out_size) {
  (void)in_sizes; (void)n_in; (void)out_size;
  EncodeFn enc = nullptr;
  cudaDriverEntryPointQueryResult qr;
  cudaGetDriverEntryPoint("cuTensorMapEncodeTiled", (void**)&enc, cudaEnableDefault, &qr);
  void *sm, *oa, *ob;
  cudaGetSymbolAddress(&sm, g_s);
  cudaGetSymbolAddress(&oa, g_oa);
  cudaGetSymbolAddress(&ob, g_ob);
  void* kvb = ((Small*)sm)->kvb;
  const void *xA = d_in[0], *wqkv = d_in[1], *woA = d_in[2], *xB = d_in[3], *wq = d_in[4], *wk = d_in[5], *wv = d_in[6], *woB = d_in[7];
  Maps mp;
  mapnd<3>(enc, &mp.xBh, xB, {{64, 1, 64}, {2048, 1024, 64}, {16, 64, 2}});
  mapnd<2>(enc, &mp.wqh, wq, {{1024, 1, 64}, {1024, 1024, 128}});
  mapnd<2>(enc, &mp.wkv[0], wk, {{64, 1, 64}, {512, 64, 256}});
  mapnd<2>(enc, &mp.wkv[1], wv, {{64, 1, 64}, {512, 64, 256}});
  mapnd<2>(enc, &mp.kvS, kvb, {{64, 1, 16}, {2048, 64, 64}}, CU_TENSOR_MAP_SWIZZLE_NONE);
  mapnd<2>(enc, &mp.kvb, kvb, {{64, 1, 64}, {2048, 64, 128}});
  mapnd<2>(enc, &mp.x[0], xB, {{1024, 1, 64}, {2048, 1024, 128}});
  mapnd<2>(enc, &mp.x[1], xA, {{1024, 1, 64}, {2048, 1024, 128}});
  mapnd<3>(enc, &mp.w[0], wq, {{64, 1, 64}, {1024, 1024, 64}, {16, 64, 2}});
  mapnd<3>(enc, &mp.w[1], wqkv, {{1024, 1, 64}, {1024, 3072, 64}, {3, 1024, 2}});
  mapnd<3>(enc, &mp.w[2], wqkv, {{64, 1, 64}, {1024, 3072, 64}, {48, 64, 2}});
  mapnd<2>(enc, &mp.oL[0], oa, {{1024, 1, 64}, {2048, 1024, 128}});
  mapnd<2>(enc, &mp.oL[1], ob, {{1024, 1, 64}, {2048, 1024, 128}});
  mapnd<5>(enc, &mp.wo[0], woA, {{64, 1, 64}, {32, 1024, 32}, {4, 256 * 1024, 1}, {8, 32 * 1024, 2}, {16, 64, 2}});
  mapnd<5>(enc, &mp.wo[1], woB, {{64, 1, 64}, {32, 1024, 32}, {4, 32 * 1024, 1}, {8, 128 * 1024, 2}, {16, 64, 2}});
  mapnd<2>(enc, &mp.st[0], oa, {{1024, 1, 64}, {2048, 1024, 64}});
  mapnd<2>(enc, &mp.st[1], d_out, {{2048, 1, 64}, {2048, 2048, 64}});
  mapnd<3>(enc, &mp.obH, ob, {{64, 1, 64}, {2048, 1024, 64}, {16, 64, 4}});
  mapnd<2>(enc, &mp.obS, ob, {{1024, 1, 32}, {2048, 1024, 64}}, CU_TENSOR_MAP_SWIZZLE_64B);
  cudaFuncSetAttribute(fused_kernel, cudaFuncAttributeMaxDynamicSharedMemorySize, SMEM_BYTES);
  fused_kernel<<<128, 512, SMEM_BYTES, cudaStreamPerThread>>>(0, (Small*)sm, mp);
}
```
